```python
import torch

def _softmax(x, axis=-1):
    return torch.softmax(x, dim=axis)
def _gelu(x):
    return torch.nn.functional.gelu(x, approximate="tanh")
def _silu(x):
    return torch.nn.functional.silu(x)
def _sigmoid(x):
    return torch.sigmoid(x)
def _layernorm(x, axis=-1, eps=1e-5):
    m = x.mean(dim=axis, keepdim=True)
    v = x.var(dim=axis, keepdim=True, unbiased=False)
    return (x - m) / torch.sqrt(v + eps)
def _scatter_add(tgt, idx, src, axis=0):
    return tgt.clone().index_add_(axis, idx, src)
def _segment_sum(src, seg, n):
    out = torch.zeros((n,) + src.shape[1:], dtype=src.dtype)
    return out.index_add_(0, seg, src)
def _pad(x, pw):
    flat = tuple(v for pair in reversed(pw) for v in pair)
    return torch.nn.functional.pad(x, flat)

kernel_name = 'parallel_sum__ssm_conv_s5__glu_gated_swiglu__prompt'

def setup_inputs():

    _w = (lambda a: (lambda t: t.to(torch.bfloat16) if t.is_floating_point() else t)(torch.as_tensor(a)))
    def _A_setup():
        B, S, D = 1, 2048, 576
        P = D
        Lambda_re = -0.5 * (lambda _x: torch.exp(torch.as_tensor(_x)))((lambda *s: torch.randn(*s, dtype=torch.bfloat16) * 0.2)(P))
        Lambda_im = (lambda *s: torch.randn(*s, dtype=torch.bfloat16) * 0.8)(P) * 1.0
        B_re = (lambda *s: torch.randn(*s, dtype=torch.bfloat16) * 0.2)(P, D) * (D ** -0.5)
        B_im = (lambda *s: torch.randn(*s, dtype=torch.bfloat16) * 0.2)(P, D) * (D ** -0.5)
        C_re = (lambda *s: torch.randn(*s, dtype=torch.bfloat16) * 0.2)(D, P) * (P ** -0.5)
        C_im = (lambda *s: torch.randn(*s, dtype=torch.bfloat16) * 0.2)(D, P) * (P ** -0.5)
        log_dt = (lambda *s: torch.randn(*s, dtype=torch.bfloat16) * 0.2)(P) * 0.3 - 2.0
        Dskip = (lambda *s: torch.randn(*s, dtype=torch.bfloat16) * 0.05)(D)
        return {
            "x": _w((lambda *s: torch.randn(*s, dtype=torch.bfloat16) * 0.05)(B, S, D)),
            "Lambda_re": _w(Lambda_re),
            "Lambda_im": _w(Lambda_im),
            "B_re": _w(B_re),
            "B_im": _w(B_im),
            "C_re": _w(C_re),
            "C_im": _w(C_im),
            "log_dt": _w(log_dt),
            "Dskip": _w(Dskip),
        }
    _A_in = _A_setup()

    def _B_setup():
        B, S, D, F = 1, 2048, 576, 4608
        return {
            "x": _w((lambda *s: torch.randn(*s, dtype=torch.bfloat16) * 0.05)(B, S, D)),
            "w1": _w((lambda *s: torch.randn(*s, dtype=torch.bfloat16) * 0.4)(D, F) * (2.0 / D) ** 0.5),
            "w3": _w((lambda *s: torch.randn(*s, dtype=torch.bfloat16) * 0.4)(D, F) * (2.0 / D) ** 0.5),
            "w2": _w((lambda *s: torch.randn(*s, dtype=torch.bfloat16) * 0.4)(F, D) * (2.0 / F) ** 0.5),
        }
    _B_in = _B_setup()

    return {
        "A_x": _A_in["x"],
        "A_Lambda_re": _A_in["Lambda_re"],
        "A_Lambda_im": _A_in["Lambda_im"],
        "A_B_re": _A_in["B_re"],
        "A_B_im": _A_in["B_im"],
        "A_C_re": _A_in["C_re"],
        "A_C_im": _A_in["C_im"],
        "A_log_dt": _A_in["log_dt"],
        "A_Dskip": _A_in["Dskip"],
        "B_x": _B_in["x"],
        "B_w1": _B_in["w1"],
        "B_w3": _B_in["w3"],
        "B_w2": _B_in["w2"],
    }

def reference(A_x, A_Lambda_re, A_Lambda_im, A_B_re, A_B_im, A_C_re, A_C_im, A_log_dt, A_Dskip, B_x, B_w1, B_w3, B_w2):
    def _A_ref(x, Lambda_re, Lambda_im, B_re, B_im, C_re, C_im, log_dt, Dskip):
        Bsz, L, H = x.shape
        Lam = Lambda_re + 1j * Lambda_im
        Bmat = B_re + 1j * B_im
        Cmat = C_re + 1j * C_im
        dt = torch.exp(log_dt)
        Lam_bar = torch.exp(dt * Lam)
        B_bar = ((Lam_bar - 1.0) / Lam)[:, None] * Bmat
        Bu = torch.einsum("bld,pd->blp", x + 0j, B_bar)
        h = torch.zeros_like(Bu[:, 0, :])
        hs = []
        for t in range(L):
            h = Lam_bar[None, :] * h + Bu[:, t, :]
            hs.append(h)
        hseq = torch.stack(hs, 1)
        y = 2.0 * torch.einsum("blp,dp->bld", hseq, Cmat).real + x * Dskip[None, None, :]
        return y

    def _B_ref(x, w1, w3, w2):
        gate = torch.einsum("bsd,df->bsf", x, w1)
        up = torch.einsum("bsd,df->bsf", x, w3)
        h = _silu(gate) * up
        out = torch.einsum("bsf,fd->bsd", h, w2)
        return out

    x = A_x
    xn = _layernorm(x, axis=-1)
    return x + _A_ref(xn, A_Lambda_re, A_Lambda_im, A_B_re, A_B_im, A_C_re, A_C_im, A_log_dt, A_Dskip) + _B_ref(xn, B_w1, B_w3, B_w2)
```

```cpp
#include <cuda_runtime.h>
#include <cuda.h>
#include <cuda_bf16.h>
#include <stdint.h>

#define X_NRED 8
#define MAPPING 1
#define FENCE_ALL 1
#define USE_TANH 1
#define STAGE_FAST 1
#define X_NINIT 24
#define CARRY_DELAY 1000
#define X_PFX 1
#define X_PFB 1
#define X_PFM 1
#define RED_DEPTH 3
#define XDUMMY 1
#define CONS_REGS 240
#define AUX_REGS 24
#define SLICE(bx) (MAPPING ? (bx) >> 4 : ((bx) >> 1) & 7)
#define PAIR(bx) (MAPPING ? ((bx) >> 1) & 7 : (bx) >> 4)
#define STR2(x) #x
#define STR(x) STR2(x)

namespace {

constexpr int L_ = 2048, D_ = 576, F_ = 4608;
constexpr int NSLOT = 6;
constexpr int NBAR = 12;
constexpr int SLOT_B = 8192;
constexpr uint32_t OFF_PARK = 0;
constexpr uint32_t OFF_H = 131072;
constexpr uint32_t OFF_XSLOT = 147456;
constexpr uint32_t OFF_RING = 167936;
constexpr uint32_t OFF_BAR = OFF_RING + NSLOT * SLOT_B;
constexpr uint32_t B_FULL = OFF_BAR, B_EMPTY = B_FULL + 8 * NBAR, B_XFULL = B_EMPTY + 8 * NBAR, B_XDONE = B_XFULL + 8 * 18,
                   B_URDY = B_XDONE + 8, B_HRDY = B_URDY + 8, B_UFREE = B_HRDY + 8, B_SFULL = B_UFREE + 8, B_SEMPTY = B_SFULL + 32, B_CARRY = B_SEMPTY + 32,
                   B_XROW = B_CARRY + 24, B_IDONE = B_XROW + 8, B_END = B_IDONE + 8;
constexpr uint32_t OFF_U0 = OFF_BAR + 512;
constexpr uint32_t OFF_U = 65536 - 8 * 1024;
constexpr uint32_t OFF_COEF = OFF_U0 + 8192, OFF_STAT = OFF_COEF + 72 * 8;
constexpr uint32_t OFF_XROW = 65536 - 17 * 1152;
constexpr uint32_t OFF_REM = (OFF_STAT + 128 + 127) & ~127u;
constexpr uint32_t OFF_TIM = OFF_REM + 2048;
constexpr uint32_t SMEM_BYTES = OFF_TIM;
static_assert(B_END <= OFF_U0 && OFF_U0 % 128 == 0 && OFF_XROW % 16 == 0 && SMEM_BYTES <= 232448, "smem map");
constexpr uint32_t SB_LO = 1024;
constexpr uint32_t DESC0 = (SB_LO >> 4) | (1u << 16);
constexpr uint32_t DHI_SW128 = 0x40000040u;
constexpr uint32_t DHI_NOSW = 0x00000008u;
constexpr uint32_t DHI_HT = 0x00000008u;

struct Params {
  CUtensorMap mx, mw1, mw3, mw2, mbre, mbim, mcre, mcim, mcre8, mcim8, mout;
  const __nv_bfloat16 *x, *lre, *lim, *logdt, *dskip;
  float* out;
};

__device__ unsigned long long g_done;
__device__ unsigned int g_initcnt[16];
__device__ uint4 g_E[8 * 3 * 16 * 24];
#define TSTAMP(i)
#define TRC(p)
#define TRP(a)

__device__ __forceinline__ long long gtime() { long long t; asm volatile("mov.u64 %0, %%globaltimer;" : "=l"(t)); return t; }
__device__ __forceinline__ uint32_t smem_u32(const void* p) { return (uint32_t)__cvta_generic_to_shared(p); }
__device__ __forceinline__ void mbar_init(uint32_t bar, uint32_t cnt) { asm volatile("mbarrier.init.shared::cta.b64 [%0], %1;" :: "r"(bar), "r"(cnt) : "memory"); }
__device__ __forceinline__ void mbar_expect_tx(uint32_t bar, uint32_t bytes) { asm volatile("mbarrier.arrive.expect_tx.shared::cta.b64 _, [%0], %1;" :: "r"(bar), "r"(bytes) : "memory"); }
__device__ __forceinline__ void mbar_arrive(uint32_t bar) { asm volatile("mbarrier.arrive.shared::cta.b64 _, [%0];" :: "r"(bar) : "memory"); }
__device__ __forceinline__ void mbar_arrive_rem(uint32_t cbar) { asm volatile("mbarrier.arrive.shared::cluster.b64 _, [%0];" :: "r"(cbar) : "memory"); }
__device__ __forceinline__ void mbar_wait(uint32_t bar, uint32_t parity) {
  asm volatile("{\n.reg .pred p;\n.reg .u32 c;\n"
    "mbarrier.try_wait.parity.shared::cta.b64 p, [%0], %1;\n@p bra LAB_DONE;\nmov.u32 c, 0;\n"
    "LAB_WAIT:\nmbarrier.try_wait.parity.shared::cta.b64 p, [%0], %1;\n@p bra LAB_DONE;\n"
    "add.u32 c, c, 1;\nsetp.lt.u32 p, c, 2000000;\n@p bra LAB_WAIT;\ntrap;\nLAB_DONE:\n}" :: "r"(bar), "r"(parity) : "memory");
}
__device__ __forceinline__ void mbar_probe(uint32_t bar, uint32_t parity) {
  asm volatile("mbarrier.test_wait.parity.shared::cta.b64 PROBE, [%0], %1;" :: "r"(bar), "r"(parity) : "memory");
}
__device__ __forceinline__ void mbar_finish(uint32_t bar, uint32_t parity) {
  asm volatile("{\n.reg .u32 c;\n@PROBE bra LAB_DONE;\nmov.u32 c, 0;\n"
    "LAB_WAIT:\nmbarrier.try_wait.parity.shared::cta.b64 PROBE, [%0], %1;\n@PROBE bra LAB_DONE;\n"
    "add.u32 c, c, 1;\nsetp.lt.u32 PROBE, c, 2000000;\n@PROBE bra LAB_WAIT;\ntrap;\nLAB_DONE:\n}" :: "r"(bar), "r"(parity) : "memory");
}
__device__ __forceinline__ void flag_wait(const unsigned int* p, unsigned int v) {
  asm volatile("{\n.reg .pred q;\n.reg .u32 c, t;\nmov.u32 c, 0;\n"
    "LAB_WAIT:\nld.acquire.gpu.global.u32 t, [%0];\nsetp.eq.u32 q, t, %1;\n@q bra LAB_DONE;\n"
    "nanosleep.u32 64;\nadd.u32 c, c, 1;\nsetp.lt.u32 q, c, 4000000;\n@q bra LAB_WAIT;\ntrap;\nLAB_DONE:\n}" :: "l"(p), "r"(v) : "memory");
}
__device__ __forceinline__ void tma_load(uint32_t dst, const CUtensorMap* m, uint32_t bar, int c0, int c1) {
  asm volatile("cp.async.bulk.tensor.2d.shared::cluster.global.mbarrier::complete_tx::bytes [%0], [%1, {%3, %4}], [%2];"
    :: "r"(dst), "l"(m), "r"(bar), "r"(c0), "r"(c1) : "memory");
}
__device__ __forceinline__ void tma_load_mc(uint32_t dst, const CUtensorMap* m, uint32_t bar, int c0, int c1) {
  asm volatile("cp.async.bulk.tensor.2d.shared::cluster.global.mbarrier::complete_tx::bytes.multicast::cluster [%0], [%1, {%3, %4}], [%2], %5;"
    :: "r"(dst), "l"(m), "r"(bar), "r"(c0), "r"(c1), "h"((uint16_t)3) : "memory");
}
__device__ __forceinline__ void tma_prefetch(const CUtensorMap* m, int c0, int c1) {
  asm volatile("cp.async.bulk.prefetch.tensor.2d.L2.global [%0, {%1, %2}];" :: "l"(m), "r"(c0), "r"(c1) : "memory");
}
__device__ __forceinline__ int fresh_ctaid() { int r; asm volatile("mov.u32 %0, %%ctaid.x;" : "=r"(r)); return r; }
__device__ __forceinline__ bool elect() {
  uint32_t r; asm volatile("{\n.reg .pred p;\nelect.sync _|p, 0xffffffff;\nselp.u32 %0, 1, 0, p;\n}" : "=r"(r)); return r;
}
__device__ __forceinline__ void wg_fence() { asm volatile("wgmma.fence.sync.aligned;" ::: "memory"); }
__device__ __forceinline__ void wg_commit() { asm volatile("wgmma.commit_group.sync.aligned;" ::: "memory"); }
template<int N> __device__ __forceinline__ void wg_wait() { asm volatile("wgmma.wait_group.sync.aligned %0;" :: "n"(N) : "memory"); }
__device__ __forceinline__ void fence_async_smem() { asm volatile("fence.proxy.async.shared::cta;" ::: "memory"); }
__device__ __forceinline__ uint64_t mkdesc(uint32_t lo, uint32_t hi) { return ((uint64_t)hi << 32) | lo; }
template<int N> __device__ __forceinline__ void pin(float (&d)[N]) {
#pragma unroll
  for (int i = 0; i < N; i++) asm volatile("" : "+f"(d[i]) :: "memory");
}
__device__ __forceinline__ uint32_t pack_bf16(float lo, float hi) { uint32_t r; asm("cvt.rn.bf16x2.f32 %0, %1, %2;" : "=r"(r) : "f"(hi), "f"(lo)); return r; }
__device__ __forceinline__ float bf_round(float v) { return __bfloat162float(__float2bfloat16_rn(v)); }
__device__ __forceinline__ float bf_lo(uint32_t v) { return __uint_as_float(v << 16); }
__device__ __forceinline__ float bf_hi(uint32_t v) { return __uint_as_float(v & 0xffff0000u); }
__device__ __forceinline__ uint32_t hmul2_bf16(uint32_t a, uint32_t b) { uint32_t r; asm("mul.rn.bf16x2 %0, %1, %2;" : "=r"(r) : "r"(a), "r"(b)); return r; }
__device__ __forceinline__ uint32_t hsub2_bf16(uint32_t a, uint32_t b) { uint32_t r; asm("sub.rn.bf16x2 %0, %1, %2;" : "=r"(r) : "r"(a), "r"(b)); return r; }
__device__ __forceinline__ void sts64(uint32_t a, uint32_t x, uint32_t y) { asm volatile("st.shared.v2.b32 [%0], {%1, %2};" :: "r"(a), "r"(x), "r"(y) : "memory"); }
__device__ __forceinline__ void sts64f(uint32_t a, float x, float y) { asm volatile("st.shared.v2.f32 [%0], {%1, %2};" :: "r"(a), "f"(x), "f"(y) : "memory"); }
__device__ __forceinline__ void sts128(uint32_t a, const uint32_t* v) { asm volatile("st.shared.v4.b32 [%0], {%1, %2, %3, %4};" :: "r"(a), "r"(v[0]), "r"(v[1]), "r"(v[2]), "r"(v[3]) : "memory"); }
__device__ __forceinline__ void lds128(uint32_t* v, uint32_t a) { asm volatile("ld.shared.v4.b32 {%0, %1, %2, %3}, [%4];" : "=r"(v[0]), "=r"(v[1]), "=r"(v[2]), "=r"(v[3]) : "r"(a) : "memory"); }
__device__ __forceinline__ void sts32f(uint32_t a, float x) { asm volatile("st.shared.f32 [%0], %1;" :: "r"(a), "f"(x) : "memory"); }
__device__ __forceinline__ void lds128f(float* v, uint32_t a) { asm volatile("ld.shared.v4.f32 {%0, %1, %2, %3}, [%4];" : "=f"(v[0]), "=f"(v[1]), "=f"(v[2]), "=f"(v[3]) : "r"(a) : "memory"); }

__device__ __forceinline__ void mma16816(float (&d)[4], const uint32_t* a, uint32_t b0, uint32_t b1) {
  asm volatile("mma.sync.aligned.m16n8k16.row.col.f32.bf16.bf16.f32 {%0, %1, %2, %3}, {%4, %5, %6, %7}, {%8, %9}, {%0, %1, %2, %3};"
    : "+f"(d[0]), "+f"(d[1]), "+f"(d[2]), "+f"(d[3]) : "r"(a[0]), "r"(a[1]), "r"(a[2]), "r"(a[3]), "r"(b0), "r"(b1));
}
__device__ __forceinline__ float std_of(float var) { float q; asm("sqrt.approx.ftz.f32 %0, %1;" : "=f"(q) : "f"(bf_round(bf_round(var) + 1e-5f))); return q; }
__device__ __forceinline__ float rcp_bf(float q) { float r; asm("rcp.approx.ftz.f32 %0, %1;" : "=f"(r) : "f"(bf_round(q))); return r; }

template<int TB> __device__ __forceinline__ void wg_rs48(float (&d)[24], const uint32_t* a, uint64_t db) {
  asm volatile("{\n.reg .pred p;\nsetp.ne.b32 p, 1, 0;\n"
  "wgmma.mma_async.sync.aligned.m64n48k16.f32.bf16.bf16 "
  "{%0, %1, %2, %3, %4, %5, %6, %7, %8, %9, %10, %11, %12, %13, %14, %15, %16, %17, %18, %19, %20, %21, %22, %23}, "
  "{%24, %25, %26, %27}, %28, p, 1, 1, %29;\n}\n"
  : "+f"(d[0]), "+f"(d[1]), "+f"(d[2]), "+f"(d[3]), "+f"(d[4]), "+f"(d[5]), "+f"(d[6]), "+f"(d[7]),
    "+f"(d[8]), "+f"(d[9]), "+f"(d[10]), "+f"(d[11]), "+f"(d[12]), "+f"(d[13]), "+f"(d[14]), "+f"(d[15]),
    "+f"(d[16]), "+f"(d[17]), "+f"(d[18]), "+f"(d[19]), "+f"(d[20]), "+f"(d[21]), "+f"(d[22]), "+f"(d[23])
  : "r"(a[0]), "r"(a[1]), "r"(a[2]), "r"(a[3]), "l"(db), "n"(TB));
}
template<int TB> __device__ __forceinline__ void wg_rs48_z(float (&d)[24], const uint32_t* a, uint64_t db) {
  asm volatile("{\n.reg .pred p;\nsetp.ne.b32 p, 0, 0;\n"
  "wgmma.mma_async.sync.aligned.m64n48k16.f32.bf16.bf16 "
  "{%0, %1, %2, %3, %4, %5, %6, %7, %8, %9, %10, %11, %12, %13, %14, %15, %16, %17, %18, %19, %20, %21, %22, %23}, "
  "{%24, %25, %26, %27}, %28, p, 1, 1, %29;\n}\n"
  : "=f"(d[0]), "=f"(d[1]), "=f"(d[2]), "=f"(d[3]), "=f"(d[4]), "=f"(d[5]), "=f"(d[6]), "=f"(d[7]),
    "=f"(d[8]), "=f"(d[9]), "=f"(d[10]), "=f"(d[11]), "=f"(d[12]), "=f"(d[13]), "=f"(d[14]), "=f"(d[15]),
    "=f"(d[16]), "=f"(d[17]), "=f"(d[18]), "=f"(d[19]), "=f"(d[20]), "=f"(d[21]), "=f"(d[22]), "=f"(d[23])
  : "r"(a[0]), "r"(a[1]), "r"(a[2]), "r"(a[3]), "l"(db), "n"(TB));
}
template<int TB> __device__ __forceinline__ void wg_rs64(float (&d)[32], const uint32_t* a, uint64_t db) {
  asm volatile("{\n.reg .pred p;\nsetp.ne.b32 p, 1, 0;\n"
  "wgmma.mma_async.sync.aligned.m64n64k16.f32.bf16.bf16 "
  "{%0, %1, %2, %3, %4, %5, %6, %7, %8, %9, %10, %11, %12, %13, %14, %15, %16, %17, %18, %19, %20, %21, %22, %23, %24, %25, %26, %27, %28, %29, %30, %31}, "
  "{%32, %33, %34, %35}, %36, p, 1, 1, %37;\n}\n"
  : "+f"(d[0]), "+f"(d[1]), "+f"(d[2]), "+f"(d[3]), "+f"(d[4]), "+f"(d[5]), "+f"(d[6]), "+f"(d[7]),
    "+f"(d[8]), "+f"(d[9]), "+f"(d[10]), "+f"(d[11]), "+f"(d[12]), "+f"(d[13]), "+f"(d[14]), "+f"(d[15]),
    "+f"(d[16]), "+f"(d[17]), "+f"(d[18]), "+f"(d[19]), "+f"(d[20]), "+f"(d[21]), "+f"(d[22]), "+f"(d[23]),
    "+f"(d[24]), "+f"(d[25]), "+f"(d[26]), "+f"(d[27]), "+f"(d[28]), "+f"(d[29]), "+f"(d[30]), "+f"(d[31])
  : "r"(a[0]), "r"(a[1]), "r"(a[2]), "r"(a[3]), "l"(db), "n"(TB));
}
template<int TB> __device__ __forceinline__ void wg_rs64_z(float (&d)[32], const uint32_t* a, uint64_t db) {
  asm volatile("{\n.reg .pred p;\nsetp.ne.b32 p, 0, 0;\n"
  "wgmma.mma_async.sync.aligned.m64n64k16.f32.bf16.bf16 "
  "{%0, %1, %2, %3, %4, %5, %6, %7, %8, %9, %10, %11, %12, %13, %14, %15, %16, %17, %18, %19, %20, %21, %22, %23, %24, %25, %26, %27, %28, %29, %30, %31}, "
  "{%32, %33, %34, %35}, %36, p, 1, 1, %37;\n}\n"
  : "=f"(d[0]), "=f"(d[1]), "=f"(d[2]), "=f"(d[3]), "=f"(d[4]), "=f"(d[5]), "=f"(d[6]), "=f"(d[7]),
    "=f"(d[8]), "=f"(d[9]), "=f"(d[10]), "=f"(d[11]), "=f"(d[12]), "=f"(d[13]), "=f"(d[14]), "=f"(d[15]),
    "=f"(d[16]), "=f"(d[17]), "=f"(d[18]), "=f"(d[19]), "=f"(d[20]), "=f"(d[21]), "=f"(d[22]), "=f"(d[23]),
    "=f"(d[24]), "=f"(d[25]), "=f"(d[26]), "=f"(d[27]), "=f"(d[28]), "=f"(d[29]), "=f"(d[30]), "=f"(d[31])
  : "r"(a[0]), "r"(a[1]), "r"(a[2]), "r"(a[3]), "l"(db), "n"(TB));
}
template<int TA, int TB> __device__ __forceinline__ void wg_ss64(float (&d)[32], uint64_t da, uint64_t db) {
  asm volatile("{\n.reg .pred p;\nsetp.ne.b32 p, 1, 0;\n"
  "wgmma.mma_async.sync.aligned.m64n64k16.f32.bf16.bf16 "
  "{%0, %1, %2, %3, %4, %5, %6, %7, %8, %9, %10, %11, %12, %13, %14, %15, %16, %17, %18, %19, %20, %21, %22, %23, %24, %25, %26, %27, %28, %29, %30, %31}, "
  "%32, %33, p, 1, 1, %35, %34;\n}\n"
  : "+f"(d[0]), "+f"(d[1]), "+f"(d[2]), "+f"(d[3]), "+f"(d[4]), "+f"(d[5]), "+f"(d[6]), "+f"(d[7]),
    "+f"(d[8]), "+f"(d[9]), "+f"(d[10]), "+f"(d[11]), "+f"(d[12]), "+f"(d[13]), "+f"(d[14]), "+f"(d[15]),
    "+f"(d[16]), "+f"(d[17]), "+f"(d[18]), "+f"(d[19]), "+f"(d[20]), "+f"(d[21]), "+f"(d[22]), "+f"(d[23]),
    "+f"(d[24]), "+f"(d[25]), "+f"(d[26]), "+f"(d[27]), "+f"(d[28]), "+f"(d[29]), "+f"(d[30]), "+f"(d[31])
  : "l"(da), "l"(db), "n"(TB), "n"(TA));
}
template<int TA, int TB> __device__ __forceinline__ void wg_ss64_z(float (&d)[32], uint64_t da, uint64_t db) {
  asm volatile("{\n.reg .pred p;\nsetp.ne.b32 p, 0, 0;\n"
  "wgmma.mma_async.sync.aligned.m64n64k16.f32.bf16.bf16 "
  "{%0, %1, %2, %3, %4, %5, %6, %7, %8, %9, %10, %11, %12, %13, %14, %15, %16, %17, %18, %19, %20, %21, %22, %23, %24, %25, %26, %27, %28, %29, %30, %31}, "
  "%32, %33, p, 1, 1, %35, %34;\n}\n"
  : "=f"(d[0]), "=f"(d[1]), "=f"(d[2]), "=f"(d[3]), "=f"(d[4]), "=f"(d[5]), "=f"(d[6]), "=f"(d[7]),
    "=f"(d[8]), "=f"(d[9]), "=f"(d[10]), "=f"(d[11]), "=f"(d[12]), "=f"(d[13]), "=f"(d[14]), "=f"(d[15]),
    "=f"(d[16]), "=f"(d[17]), "=f"(d[18]), "=f"(d[19]), "=f"(d[20]), "=f"(d[21]), "=f"(d[22]), "=f"(d[23]),
    "=f"(d[24]), "=f"(d[25]), "=f"(d[26]), "=f"(d[27]), "=f"(d[28]), "=f"(d[29]), "=f"(d[30]), "=f"(d[31])
  : "l"(da), "l"(db), "n"(TB), "n"(TA));
}

struct Pipe {
  uint32_t full, rel;
  bool sig;
  __device__ __forceinline__ void wait(int b, uint32_t ph) { mbar_wait(full + 8 * b, ph); }
  __device__ __forceinline__ void probe(int b, uint32_t ph) { mbar_probe(full + 8 * b, ph); }
  __device__ __forceinline__ void finish(int b, uint32_t ph) { mbar_finish(full + 8 * b, ph); }
  static __device__ __forceinline__ constexpr uint32_t desc(int b) { return DESC0 + ((b < NSLOT ? OFF_RING + b * SLOT_B : OFF_PARK + (b - NSLOT) * SLOT_B) >> 4); }
  __device__ __forceinline__ void release(int b) {
    if (sig) {
      mbar_arrive_rem(rel + 8 * b);
    }
  }
};

template<int N, int S0, int PREV, bool AMOD = false, class PieceF, class DoneF>
__device__ __forceinline__ void kloop(float (&acc)[N / 2], const uint32_t (&A)[144], Pipe& p, uint32_t ph, PieceF piece, DoneF done0) {
#pragma unroll
  for (int kk = 0; kk < 9; kk++) {
    const int nb = N == 64 ? (S0 + kk + 1) % NSLOT : (kk + 1) % 9;
    const uint32_t nph = ph ^ (N == 64 ? ((S0 + kk + 1) / NSLOT) & 1 : kk == 8);
    p.probe(nb, nph);
    if (FENCE_ALL || AMOD || kk == 0) wg_fence();
#pragma unroll
    for (int q = 0; q < 4; q++) {
      if constexpr (N == 64) {
        const uint64_t db = mkdesc(p.desc((S0 + kk) % NSLOT) + q * 128, DHI_SW128);
        if (kk == 0 && q == 0) wg_rs64_z<1>(acc, &A[0], db); else wg_rs64<1>(acc, &A[kk * 16 + q * 4], db);
      } else {
        const uint64_t db = mkdesc((kk < NSLOT ? p.desc(kk) : DESC0 + ((OFF_XSLOT + (kk - NSLOT) * 6144) >> 4)) + q * 2, DHI_SW128);
        if (kk == 0 && q == 0) wg_rs48_z<0>(acc, &A[0], db); else wg_rs48<0>(acc, &A[kk * 16 + q * 4], db);
      }
      if (q == 3) wg_commit();
      piece(kk, q);
    }
    const int prev = kk == 0 ? PREV : N == 64 ? (S0 + kk - 1) % NSLOT : (S0 == 2 && kk > NSLOT) ? -2 : kk - 1;
    if (prev != -1) wg_wait<1>();
    if (prev >= 0) p.release(prev);
    p.finish(nb, nph);
    TRC(p);
    if (kk == 0) done0();
  }
}

}

__global__ void __cluster_dims__(2, 1, 1) __launch_bounds__(384, 1) fused_s5_swiglu_kernel(const __grid_constant__ Params P) {
  extern __shared__ __align__(1024) uint8_t smem_raw[];
  asm volatile(".reg .pred PROBE;");
  const uint32_t sb = smem_u32(smem_raw);
  if ((sb & 0xFFFFFFu) != SB_LO) asm volatile("trap;");
  const int tid = threadIdx.x;
  const int wg = __shfl_sync(0xffffffff, tid >> 7, 0);
  const int rank = blockIdx.x & 1;
  const int cl = blockIdx.x >> 1;
  const int sl = MAPPING ? cl >> 3 : cl & 7, mp = MAPPING ? cl & 7 : cl >> 3;
  const int mb = mp * 2 + rank;

  if (tid == 256) {
    TSTAMP(0);
#pragma unroll
    for (int i = 0; i < 18; i++) mbar_init(sb + B_XFULL + 8 * i, 1);
    asm volatile("fence.mbarrier_init.release.cluster;" ::: "memory");
  } else if (tid == 288) {
#pragma unroll
    for (int i = 0; i < NBAR; i++) { mbar_init(sb + B_FULL + 8 * i, 1); mbar_init(sb + B_EMPTY + 8 * i, 4); }
    asm volatile("fence.mbarrier_init.release.cluster;" ::: "memory");
  } else if (tid == 320) {
#pragma unroll
    for (int i = 0; i < 4; i++) { mbar_init(sb + B_SFULL + 8 * i, 4); mbar_init(sb + B_SEMPTY + 8 * i, 1); }
#pragma unroll
    for (int i = 0; i < 3; i++) mbar_init(sb + B_CARRY + 8 * i, 1);
    mbar_init(sb + B_XDONE, 11); mbar_init(sb + B_URDY, 8); mbar_init(sb + B_HRDY, 3); mbar_init(sb + B_UFREE, 3);
    mbar_init(sb + B_XROW, 2); mbar_init(sb + B_IDONE, 3);
    asm volatile("fence.mbarrier_init.release.cluster;" ::: "memory");
  }
  __syncwarp();
  asm volatile("barrier.cluster.arrive.relaxed.aligned;" ::: "memory");
  if (tid >= 256 && tid < 288) {
    if (elect()) {
#pragma unroll 1
      for (int i = 0; i < 9; i++) {
#pragma unroll
        for (int w = 0; w < 2; w++) {
          mbar_expect_tx(sb + B_XFULL + 72 * w + 8 * i, 8192);
          tma_load(sb + (w * 9 + i) * 8192, &P.mx, sb + B_XFULL + 72 * w + 8 * i, i * 64, mb * 128 + w * 64);
        }
      }
    }
    __syncwarp();
  }
  asm volatile("barrier.cluster.wait.acquire.aligned;" ::: "memory");

  if (tid == 0) TSTAMP(56);
  if (wg == 2) {
    asm volatile("setmaxnreg.dec.sync.aligned.u32 " STR(AUX_REGS) ";");
    const int warp = __shfl_sync(0xffffffff, (tid >> 5) & 3, 0), lane = tid & 31;
    if (warp == 0) {
      if (elect()) {
        const uint32_t full = sb + B_FULL, empty = sb + B_EMPTY;
        auto put = [&](int b, uint32_t dst, uint32_t ph, const CUtensorMap* m, uint32_t bytes, int c0, int c1) {
          mbar_wait(empty + 8 * b, ph);
          mbar_expect_tx(full + 8 * b, bytes);
          tma_load_mc(dst, m, full + 8 * b, c0, c1);
          TRP(trp);
        };
        {
          const int bx = fresh_ctaid(), rk = bx & 1;
          const CUtensorMap* m = &P.mbre + rk;
          const uint32_t d = sb + rk * 3072;
          int c1 = SLICE(bx) * 72;
#pragma unroll 1
          for (int t = 0; t < 3; t++, c1 += 24) {
#pragma unroll
            for (int kk = 0; kk < 9; kk++) put(kk, d + (kk < 6 ? OFF_RING + kk * SLOT_B : OFF_XSLOT + (kk - 6) * 6144), (t & 1) ^ 1, m, 6144, kk * 64, c1);
            if (t == 0) {
              const int pr = PAIR(bx);
              tma_prefetch(m, pr * 64, c1 + 24); tma_prefetch(m, pr * 64, c1 + 48);
              if (pr < 2) tma_prefetch(m, 512, c1 + 24 + pr * 24);
            }
          }
        }
        {
          const int bx = fresh_ctaid(), rk = bx & 1;
          const uint32_t d = sb + OFF_RING + rk * 4096;
          int c0 = SLICE(bx) * 576;
#pragma unroll 1
          for (int j = 0; j < 9; j++, c0 += 64) {
#pragma unroll
            for (int n = 0; n < 18; n++)
              put(n % 6, d + (n % 6) * SLOT_B, (j + n / 6) & 1, n < 9 ? &P.mw1 : &P.mw3, 8192, c0, (n % 9) * 64 + rk * 32);
          }
        }
        {
          const int bx = fresh_ctaid(), rk = bx & 1, s = SLICE(bx);
          const uint32_t d = sb + rk * 4096;
          int n0 = s * 64;
          put(11, sb + rk * 1024 + OFF_REM, 1, &P.mcre8 + rk, 2048, s * 72 + 64, n0);
          put(0, d + OFF_RING, 1, &P.mcre, 8192, s * 72, n0 + rk * 32);
          put(1, d + OFF_RING + SLOT_B, 1, &P.mcim, 8192, s * 72, n0 + rk * 32);
#pragma unroll
          for (int kk = 0; kk < 9; kk++) put((kk + 2) % 6, d + OFF_RING + ((kk + 2) % 6) * SLOT_B, kk < 4, &P.mw2, 8192, n0, s * 576 + rk * 32 + kk * 64);
#pragma unroll 1
          for (int p = 1; p < 9; p++) {
            n0 = n0 == 512 ? 0 : n0 + 64;
            const uint32_t lo = p & 1;
#pragma unroll
            for (int kk = 0; kk < 9; kk++) {
              put(kk, d + (kk < 6 ? OFF_RING + kk * SLOT_B : OFF_PARK + (kk - 6) * SLOT_B), kk < 5 ? lo : lo ^ 1, &P.mw2, 8192, n0, s * 576 + rk * 32 + kk * 64);
            }
            put(9, d + OFF_PARK + 3 * SLOT_B, lo ^ 1, &P.mcre, 8192, s * 72, n0 + rk * 32);
            put(10, d + OFF_PARK + 4 * SLOT_B, lo ^ 1, &P.mcim, 8192, s * 72, n0 + rk * 32);
            put(11, sb + rk * 1024 + OFF_REM, lo ^ 1, &P.mcre8 + rk, 2048, s * 72 + 64, n0);
          }
        }
      }
    } else {
      const int w = warp - 1;
      const int ls = lane < 24 ? lane : 0;
      float lr, li;
        {
          const int pg = sl * 72 + w * 24 + ls;
          const float dt = bf_round(expf(__bfloat162float(P.logdt[pg])));
          const float ar = __bfloat162float(P.lre[pg]), ai = __bfloat162float(P.lim[pg]);
          const float e = expf(dt * ar);
          float sn, cs; sincosf(dt * ai, &sn, &cs);
          lr = e * cs; li = e * sn;
          const float inv = 2.0f / (ar * ar + ai * ai);
          sts64f(sb + OFF_COEF + (w * 24 + ls) * 8, ((lr - 1.0f) * ar + li * ai) * inv, (li * ar - (lr - 1.0f) * ai) * inv);
          __syncwarp();
          if (lane == 0) mbar_arrive(sb + B_XDONE);
        }
      uint32_t epoch;
      { unsigned long long dn; asm volatile("ld.relaxed.gpu.global.u64 %0, [%1];" : "=l"(dn) : "l"(&g_done) : "memory"); epoch = (uint32_t)(dn >> 7) + 1u; }
      auto pf9 = [&](const CUtensorMap* m, int c0, int c1) {
        tma_prefetch(m, c0, c1 + mp * 64 + rank * 32);
        if (mp == w) tma_prefetch(m, c0, c1 + 512 + rank * 32);
      };
      auto pf_mlp = [&](int j) { if (lane == 0) { pf9(&P.mw1, sl * 576 + j * 64, 0); pf9(&P.mw3, sl * 576 + j * 64, 0); } };
      auto pf_out = [&]() {
        if (lane == 0) {
#pragma unroll 1
          for (int nb = w; nb < 9; nb += 3) {
            pf9(&P.mw2, nb * 64, sl * 576);
            if (mp == (nb & 7)) {
              tma_prefetch(&P.mcre, sl * 72, nb * 64 + rank * 32);
              tma_prefetch(&P.mcim, sl * 72, nb * 64 + rank * 32);
              tma_prefetch(rank ? &P.mcim8 : &P.mcre8, sl * 72 + 64, nb * 64);
            }
          }
        }
      };
      {
        {
          mbar_wait(sb + B_XFULL + 8 * 17, 0);
          pf_mlp(w);
          if (w == 0 && lane == 0) {
            mbar_wait(sb + B_XDONE, 0);
            fence_async_smem();
            mbar_expect_tx(sb + B_XROW, 17 * 1152);
            asm volatile("cp.async.bulk.shared::cluster.global.mbarrier::complete_tx::bytes [%0], [%1], %2, [%3];"
              :: "r"(sb + OFF_XROW), "l"(P.x + (size_t)(mb * 128 + sl * 16) * D_), "r"(16 * 1152), "r"(sb + B_XROW) : "memory");
            asm volatile("cp.async.bulk.shared::cluster.global.mbarrier::complete_tx::bytes [%0], [%1], %2, [%3];"
              :: "r"(sb + OFF_XROW + 16 * 1152), "l"(P.dskip), "r"(1152), "r"(sb + B_XROW) : "memory");
          }
          __syncwarp();
          mbar_wait(sb + B_XROW, 0);
          float4* op = reinterpret_cast<float4*>(P.out + (size_t)(mb * 128 + sl * 16) * D_) + w * 32 + lane;
          uint32_t xa = sb + OFF_XROW + (w * 32 + lane) * 8, da = xa + 16 * 1152, sa = sb + OFF_STAT;
#pragma unroll 2
          for (int it = 0; it < 24; it++, xa += 768, op += 96) {
            uint32_t v0, v1, k0, k1, m2; float rs;
            asm volatile("ld.shared.v2.b32 {%0, %1}, [%2];" : "=r"(v0), "=r"(v1) : "r"(xa));
            asm volatile("ld.shared.v2.b32 {%0, %1}, [%2];" : "=r"(k0), "=r"(k1) : "r"(da));
            asm volatile("ld.shared.v2.b32 {%0, %1}, [%2];" : "=r"(m2), "=f"(rs) : "r"(sa));
            const uint32_t d0 = hsub2_bf16(v0, m2), d1 = hsub2_bf16(v1, m2);
            const uint32_t t0 = hmul2_bf16(pack_bf16(bf_lo(d0) * rs, bf_hi(d0) * rs), k0);
            const uint32_t t1 = hmul2_bf16(pack_bf16(bf_lo(d1) * rs, bf_hi(d1) * rs), k1);
            *op = make_float4(bf_lo(v0) + bf_lo(t0), bf_hi(v0) + bf_hi(t0), bf_lo(v1) + bf_lo(t1), bf_hi(v1) + bf_hi(t1));
            da += 768; if (da >= sb + OFF_XROW + 17 * 1152) { da -= 1152; sa += 8; }
          }
          __syncwarp();
          if (lane == 0) mbar_arrive(sb + B_IDONE);
          pf_mlp(3 + w);
          if (w == 0 && lane == 0) TSTAMP(49);
        }
        mbar_wait(sb + B_URDY, 0);
        if (w == 0 && lane == 0) TSTAMP(40);
        float gr = 0.f, gi = 0.f;
        const uint32_t h0 = sb + OFF_H + (w * 3 + (ls >> 3)) * 2048 + (ls & 7) * 16;
        {
          uint32_t a = (sb + (w * 24 + ls < 8 ? OFF_U0 : OFF_U) + (w * 24 + ls) * 1024) ^ ((ls & 7) << 4), ha = h0;
#pragma unroll 1
          do {
            float v[4][4];
#pragma unroll
            for (int i = 0; i < 4; i++) lds128f(v[i], a ^ (i << 4));
            uint32_t ore[4], oim[4];
#pragma unroll
            for (int i = 0; i < 4; i++) {
              const float r0 = fmaf(lr, gr, fmaf(-li, gi, v[i][0])), i0 = fmaf(lr, gi, fmaf(li, gr, v[i][1]));
              gr = fmaf(lr, r0, fmaf(-li, i0, v[i][2])); gi = fmaf(lr, i0, fmaf(li, r0, v[i][3]));
              ore[i] = pack_bf16(r0, gr); oim[i] = pack_bf16(-i0, -gi);
            }
            if (lane < 24) { sts128(ha, ore); sts128(ha + 9 * 2048, oim); }
            ha += 128;
            a = (a ^ 64) + ((ha & 128) ? 0 : 128);
          } while ((ha & 0x780) != (SB_LO & 0x780));
        }
        uint4* const gE = g_E + (sl * 3 + w) * 16 * 24;
        if (mb < 15 && lane < 24)
          asm volatile("st.relaxed.gpu.global.v2.b64 [%0], {%1, %2};" :: "l"(gE + mb * 24 + lane),
            "l"(((uint64_t)epoch << 32) | __float_as_uint(gr)), "l"(((uint64_t)epoch << 32) | __float_as_uint(gi)) : "memory");
        __syncwarp();
        if (lane == 0) {
          mbar_arrive(sb + B_UFREE);
          asm volatile("red.release.gpu.global.add.u32 [%0], 1;" :: "l"(&g_initcnt[mb]) : "memory");
        }
        pf_mlp(6 + w);
        if (lane == 0) TSTAMP(w ? 56 + w : 46);
        if (mb > 0) {
          mbar_wait(sb + B_UFREE, 0);
          __nanosleep(CARRY_DELAY);
          float pr = lr, pi = li;
#pragma unroll
          for (int i = 0; i < 7; i++) { const float t = pr * pr - pi * pi; pi = 2.0f * pr * pi; pr = t; }
          const uint32_t eb = sb + (w < 2 ? OFF_PARK + 7 * 16384 + w * 5760 : OFF_U0);
          uint32_t tries = 0;
          bool ok;
          do {
            if (lane == 0) {
              fence_async_smem();
              mbar_expect_tx(sb + B_CARRY + 8 * w, mb * 384);
              asm volatile("cp.async.bulk.shared::cluster.global.mbarrier::complete_tx::bytes [%0], [%1], %2, [%3];"
                :: "r"(eb), "l"(gE), "r"(mb * 384), "r"(sb + B_CARRY + 8 * w) : "memory");
            }
            mbar_wait(sb + B_CARRY + 8 * w, tries & 1);
            gr = 0.f; gi = 0.f;
            uint32_t bad = 0;
#pragma unroll 1
            for (uint32_t a = eb + ls * 16; a < eb + mb * 384; a += 384) {
              uint32_t e[4]; lds128(e, a);
              bad |= (e[1] ^ epoch) | (e[3] ^ epoch);
              const float nr = fmaf(pr, gr, fmaf(-pi, gi, __uint_as_float(e[0])));
              gi = fmaf(pr, gi, fmaf(pi, gr, __uint_as_float(e[2])));
              gr = nr;
            }
            ok = __all_sync(0xffffffff, bad == 0);
            if (!ok) __nanosleep(400);
            if (++tries > 200000) asm volatile("trap;");
          } while (!ok);
          if (lane == 0) TSTAMP(w ? 60 + w : 41);
          if (lane < 24) {
            uint32_t ha = h0;
#pragma unroll 1
            for (int it = 0; it < 16; it++, ha += 128) {
              uint32_t vr[4], vi[4];
              lds128(vr, ha); lds128(vi, ha + 9 * 2048);
#pragma unroll
              for (int i = 0; i < 4; i++) {
                const float r0 = fmaf(lr, gr, -li * gi), i0 = fmaf(lr, gi, li * gr);
                gr = fmaf(lr, r0, -li * i0); gi = fmaf(lr, i0, li * r0);
                vr[i] = pack_bf16(bf_lo(vr[i]) + r0, bf_hi(vr[i]) + gr);
                vi[i] = pack_bf16(bf_lo(vi[i]) - i0, bf_hi(vi[i]) - gi);
              }
              sts128(ha, vr); sts128(ha + 9 * 2048, vi);
            }
          }
        }
        fence_async_smem();
        __syncwarp();
        if (lane == 0) mbar_arrive(sb + B_HRDY);
        pf_out();
        if (lane == 0) TSTAMP(w ? 58 + w : 42);
      }
      if (w < 2 && lane == 0) {
        flag_wait(&g_initcnt[mb], epoch * 24u);
        asm volatile("fence.proxy.async.global;" ::: "memory");
        int nb = sl;
#pragma unroll 1
        for (int p = 0; p < 9; p++) {
          const int b = p & 1;
          mbar_wait(sb + B_SFULL + (w * 2 + b) * 8, (p >> 1) & 1);
#pragma unroll 1
          for (int i = 0; i < X_NRED; i++) {
            const uint32_t src = sb + OFF_PARK + (4 + 2 * b + (i >> 2)) * 16384 + w * 8192 + (i & 3) * 2048;
            asm volatile("cp.reduce.async.bulk.tensor.4d.global.shared::cta.add.tile.bulk_group [%0, {%2, %3, %3, %4}], [%1];"
              :: "l"(&P.mout), "r"(src), "r"(nb * 64 + (i >> 2) * 32), "r"(0), "r"(mb * 16 + w * 8 + (i & 3) * 2) : "memory");
            asm volatile("cp.async.bulk.commit_group;" ::: "memory");
            if (p < 8) asm volatile("cp.async.bulk.wait_group.read " STR(RED_DEPTH) ";" ::: "memory");
          }
          if (RED_DEPTH) asm volatile("cp.async.bulk.wait_group.read 0;" ::: "memory");
          if (p < 7) mbar_arrive(sb + B_SEMPTY + (w * 2 + b) * 8);
          if (++nb == 9) nb = 0;
        }
        asm volatile("cp.async.bulk.wait_group.read 0;" ::: "memory");
        TSTAMP(44 + w);
        if (w == 0) asm volatile("red.relaxed.gpu.global.add.u64 [%0], 1;" :: "l"(&g_done) : "memory");
      }
    }
  } else {
    asm volatile("setmaxnreg.inc.sync.aligned.u32 " STR(CONS_REGS) ";");
    const int t128 = tid & 127, lane = tid & 31, warp = t128 >> 5;
    Pipe pp;
    pp.full = sb + B_FULL;
    asm volatile("mapa.shared::cluster.u32 %0, %1, %2;" : "=r"(pp.rel) : "r"(sb + B_EMPTY), "r"(t128 & 1));
    pp.sig = t128 < 2;

    uint32_t A[144];
    uint32_t m0, m1;
    float mean0, mean1, q0, q1;
    {
      const uint32_t xa = sb + wg * 73728 + (warp * 16 + (lane & 15)) * 128, xs = (lane >> 4) ^ (lane & 7);
      float sm[6][4] = {};
#pragma unroll
      for (int kk = 0; kk < 10; kk++) {
        if (kk < 9) {
          mbar_wait(sb + B_XFULL + 72 * wg + 8 * kk, 0);
          if (t128 == 0 && (kk == 0 || kk == 4 || kk == 8)) TSTAMP(50 + wg * 3 + kk / 4);
#pragma unroll
          for (int i = kk * 4; i < kk * 4 + 4; i++)
            asm volatile("ldmatrix.sync.aligned.m8n8.x4.shared.b16 {%0, %1, %2, %3}, [%4];"
              : "=r"(A[i * 4]), "=r"(A[i * 4 + 1]), "=r"(A[i * 4 + 2]), "=r"(A[i * 4 + 3]) : "r"(xa + kk * 8192 + ((xs ^ ((i & 3) * 2)) << 4)) : "memory");
        }
        if (kk > 0) {
#pragma unroll
          for (int i = kk * 4 - 4; i < kk * 4; i++) {
            mma16816(sm[i & 1], &A[i * 4], 0x3f803f80u, 0x3f803f80u);
            mma16816(sm[2 + (i & 1)], &A[i * 4], A[i * 4], A[i * 4 + 2]);
            mma16816(sm[4 + (i & 1)], &A[i * 4], A[i * 4 + 1], A[i * 4 + 3]);
          }
        }
      }
      if (t128 == 0) TSTAMP(1 + wg * 16);
      __syncwarp();
      if (lane == 0) mbar_arrive(sb + B_XDONE);
      mean0 = (sm[0][0] + sm[1][0]) * (1.0f / D_); mean1 = (sm[0][2] + sm[1][2]) * (1.0f / D_);
      q0 = (lane & 4) ? sm[2][1] + sm[3][1] : sm[2][0] + sm[3][0];
      q1 = (lane & 4) ? sm[4][3] + sm[5][3] : sm[4][2] + sm[5][2];
      m0 = pack_bf16(mean0, mean0); m1 = pack_bf16(mean1, mean1);
    }
    auto center = [&](int i0, int n) {
#pragma unroll
      for (int i = i0; i < i0 + n; i++) { A[i] = hsub2_bf16(A[i], (i & 1) ? m1 : m0); asm volatile("" : "+r"(A[i])); }
    };
    center(0, 16);
    if (t128 == 0) TSTAMP(2 + wg * 16);

    const uint32_t parkT = sb + OFF_PARK + wg * 8192 + t128 * 16;
    float c10, c11, c20, c21;
    float G[32], U[32];
    {
      float S0[24], S1[24];
      float r0, r1, cf[4];
      const uint32_t uT = (sb + OFF_U + (lane & 3) * 2048 + (wg * 64 + warp * 16 + (lane >> 2)) * 8) ^ ((lane & 3) << 5);
      const uint32_t cT = sb + OFF_COEF + (lane & 3) * 16;
      auto uepi = [&](float (&S)[24], int tile, int j, int e) {
        const float r = (e >> 1) ? r1 : r0, a = S[j * 4 + e] * r, b = S[12 + j * 4 + e] * r;
        const float cr = cf[(e & 1) * 2], ci = cf[(e & 1) * 2 + 1];
        const uint32_t ad = (uT ^ ((e & 1) << 4) ^ ((e >> 1) << 6)) + (tile * 24 + j * 8 + (e & 1)) * 1024 + (tile == 0 && j == 0 ? OFF_U0 - OFF_U : 0);
        sts64f(ad, fmaf(cr, a, -ci * b), fmaf(cr, b, ci * a));
      };
      auto uall = [&](float (&S)[24], int tile, int kk, int q) {
        if (kk >= 2 && kk <= 7 && (q & 1)) uepi(S, tile, (kk - 2) >> 1, (kk & 1) * 2 + (q >> 1));
        if ((kk == 1 || kk == 3 || kk == 5) && q == 3) lds128f(cf, cT + (tile * 24 + (kk >> 1) * 8) * 8);
      };
      pp.wait(0, 0);
      kloop<48, 0, -1, true>(S0, A, pp, 0, [&](int kk, int q) {
          if (q == 3) {
            if (kk < 8) center(kk * 16 + 16, 16);
            if (kk == 1) {
              q0 = __shfl_sync(0xffffffff, q0, (lane & 28) | (lane >> 3)); q1 = __shfl_sync(0xffffffff, q1, (lane & 28) | (lane >> 3));
              asm volatile("" : "+f"(q0), "+f"(q1));
            }
            if (kk == 2) {
              q0 = std_of(fmaxf(fmaf(-mean0, mean0, q0 * (1.0f / D_)), 0.f));
              q1 = std_of(fmaxf(fmaf(-mean1, mean1, q1 * (1.0f / D_)), 0.f));
              asm volatile("" : "+f"(q0), "+f"(q1));
            }
            if (kk == 3) { r0 = rcp_bf(q0); r1 = rcp_bf(q1); asm volatile("" : "+f"(r0), "+f"(r1)); }
            if (kk == 4 && (tid >> 5) == sl) {
              if ((lane & 3) == 0) {
                sts64(sb + OFF_STAT + (lane >> 2) * 8, m0, __float_as_uint(r0));
                sts64(sb + OFF_STAT + (lane >> 2) * 8 + 64, m1, __float_as_uint(r1));
              }
              __syncwarp();
              if (lane == 0) mbar_arrive(sb + B_XROW);
            }
          }
        }, [&]() {});
      kloop<48, 1, 8>(S1, A, pp, 1, [&](int kk, int q) {
          if (kk == 0 && q == 3) {
            mbar_wait(sb + B_XDONE, 0);
          }
          uall(S0, 0, kk, q);
        }, [&]() { pin(S0); });
      kloop<48, 2, 8>(S0, A, pp, 0, [&](int kk, int q) { uall(S1, 1, kk, q); }, [&]() { pin(S1); });
      if (t128 == 0) TSTAMP(3 + wg * 16);
      kloop<64, 0, -2>(G, A, pp, 1, [&](int kk, int q) {
          uall(S0, 2, kk, q);
          if (kk == 8 && q == 3) { __syncwarp(); if (lane == 0) mbar_arrive(sb + B_URDY); }
        }, [&]() { pin(S0); });
      c10 = r0 * 0.5f; c11 = r1 * 0.5f; c20 = r0 * c10; c21 = r1 * c11;
    }
    float T[2][4];
    auto gA = [&](int i) {
#pragma unroll
      for (int e = 0; e < 4; e++) asm volatile("tanh.approx.f32 %0, %1;" : "=f"(T[i & 1][e]) : "f"(G[4 * i + e] * (e < 2 ? c10 : c11)));
    };
    auto gB = [&](int i) {};
    auto gC = [&](int i, uint32_t& o0, uint32_t& o1) {
      const float h0 = G[4 * i] * c20, h1 = G[4 * i + 1] * c20, h2 = G[4 * i + 2] * c21, h3 = G[4 * i + 3] * c21;
      o0 = pack_bf16(fmaf(h0, T[i & 1][0], h0), fmaf(h1, T[i & 1][1], h1));
      o1 = pack_bf16(fmaf(h2, T[i & 1][2], h2), fmaf(h3, T[i & 1][3], h3));
      asm volatile("" : "+r"(o0), "+r"(o1));
    };
    auto gS = [&](uint32_t base, int i) { uint32_t o0, o1; gC(i, o0, o1); sts64(base + (i >> 1) * 2048 + (i & 1) * 8, o0, o1); };
#pragma unroll 1
    for (int j = 0; j < 8; j++) {
      const uint32_t pk = parkT + j * 16384;
      if (j == 2) mbar_wait(sb + B_IDONE, 0);
      if (j == 4) mbar_wait(sb + B_UFREE, 0);
      if (j == 7) mbar_wait(sb + B_HRDY, 0);
      kloop<64, 3, 2>(U, A, pp, j & 1, [&](int kk, int q) {
          if (kk >= 2 && q == 0) gS(pk, kk - 2);
          if (kk >= 1 && q == (kk < 8 ? 1 : 0)) gA(kk - 1);
          if (kk >= 1 && q == (kk < 8 ? 3 : 2)) gB(kk - 1);
          if (kk == 8 && q == 3) gS(pk, 7);
        }, [&]() { pin(G); });
      uint32_t sg[2][4];
      kloop<64, 0, 5>(G, A, pp, j & 1, [&](int kk, int q) {
          if (kk >= 1 && kk <= 4 && q == 0) lds128(sg[kk & 1], pk + (kk - 1) * 2048);
          if (kk >= 2 && kk <= 5 && q == 1) {
            const int i = kk - 2;
            uint32_t o[4];
#pragma unroll
            for (int e = 0; e < 4; e++) o[e] = hmul2_bf16(sg[(kk - 1) & 1][e], pack_bf16(U[8 * i + 2 * e], U[8 * i + 2 * e + 1]));
            sts128(pk + i * 2048, o);
          }
        }, [&]() { pin(U); });
      if (t128 == 0) TSTAMP(4 + j + wg * 16);
    }
    uint32_t sgk[16];
    kloop<64, 3, 2>(U, A, pp, 0, [&](int kk, int q) {
        if (kk >= 2 && q == 0) gC(kk - 2, sgk[2 * kk - 4], sgk[2 * kk - 3]);
        if (kk >= 1 && q == (kk < 8 ? 1 : 0)) gA(kk - 1);
        if (kk >= 1 && q == (kk < 8 ? 3 : 2)) gB(kk - 1);
        if (kk == 8 && q == 3) gC(7, sgk[14], sgk[15]);
      }, [&]() { pin(G); });
    if (t128 == 0) TSTAMP(12 + wg * 16);

    const uint32_t hre = DESC0 + ((OFF_H + wg * 1024) >> 4) + (((2048u >> 4) - 1u) << 16);
    const uint32_t hrem = hre + 8 * 128 + ((8u * 128u) << 16);
    const uint32_t srow = (lane >> 4) + ((lane >> 1) & 6);
    const uint32_t stT = sb + OFF_PARK + 4 * 16384 + wg * 8192 + warp * 2048 + srow * 128 + (lane & 1) * 8;
    const uint32_t stX = ((lane & 3) >> 1) ^ srow;
    auto stage = [&](float (&S)[32], int b, int j, int h) {
      sts64f(stT + (2 * b + (j >> 2)) * 16384 + ((stX ^ ((j & 3) * 2)) << 4) + h * 1024, S[j * 4 + 2 * h], S[j * 4 + 2 * h + 1]);
    };
    int pv;
    auto pass = [&](float (&acc)[32], float (&prv)[32], const bool first, const uint32_t lo, const bool last, auto piece) {
      auto slot = [&](int i) { return first && i >= 6 ? i - 6 : i; };
      auto par = [&](int i) { return first ? (i >= 6 && i < 11 ? lo ^ 1 : lo) : (i < 5 || i == 9 || i == 10) ? lo : lo ^ 1; };
#pragma unroll
      for (int g = 0; g < 11; g++) {
        const int kk = first ? g - 2 : g, c = first ? g : g - 9;
        const int nb = g < 10 ? slot(g + 1) : 0;
        const uint32_t nph = par(g + 1);
        pp.probe(nb, nph);
        wg_fence();
        if (c == 1) wg_ss64<1, 0>(acc, mkdesc(hrem, DHI_HT), mkdesc(DESC0 + (OFF_REM >> 4) + (((1024u >> 4) - 1u) << 16), DHI_NOSW));
#pragma unroll
        for (int q = 0; q < 4; q++) {
          if (c == 0 || c == 1) {
            const uint64_t da = mkdesc(hre + c * 9 * 128 + q * 256, DHI_HT), db = mkdesc(pp.desc(slot(g)) + q * 2, DHI_SW128);
            if (g == 0 && q == 0) wg_ss64_z<1, 0>(acc, da, db); else wg_ss64<1, 0>(acc, da, db);
          } else {
            const uint64_t db = mkdesc(pp.desc(slot(g)) + q * 128, DHI_SW128);
            if (g == 0 && q == 0) wg_rs64_z<1>(acc, &A[0], db); else wg_rs64<1>(acc, &A[kk * 16 + q * 4], db);
          }
          if (q == 3) wg_commit();
          piece(g, q);
        }
        if (c == 0) pp.wait(11, first ? 0 : lo ^ 1);
        wg_wait<1>();
        if (g == 0) { pp.release(first ? 5 : pv); if (!first) pp.release(11); }
        else if (!last) pp.release(slot(g - 1));
        if (g < 10 || !last) pp.finish(nb, nph);
        if (g == 0) pin(prv);
        TRC(pp);
        if (g == 1) { TRC(pp); }
      }
      pv = first ? 4 : 10;
    };
    auto wg_bar = [&]() { if (wg == 0) asm volatile("bar.sync 1, 128;" ::: "memory"); else asm volatile("bar.sync 2, 128;" ::: "memory"); };
    pass(G, U, true, 0, false, [&](int g, int q) {
        if (q == 3) {
          if (g >= 1 && g <= 7) {
#pragma unroll
            for (int i = (g > 1 ? 4 : 0); i < 8; i++) lds128(&A[(g - 1) * 16 + i * 4], parkT + (g - 1 + (i >> 2)) * 16384 + (i & 3) * 2048);
          }
          if (g >= 2 && g <= 5) {
#pragma unroll
            for (int e = 4 * (g - 2); e < 4 * (g - 1); e++) {
              A[128 + e] = hmul2_bf16(sgk[e], pack_bf16(U[2 * e], U[2 * e + 1]));
              asm volatile("" : "+r"(A[128 + e]));
            }
          }
          if (g == 9) {
            wg_bar();
#pragma unroll
            for (int b = 6; b < 11; b++) pp.release(b);
          }
        }
      });
    if (t128 == 0) TSTAMP(13 + wg * 16);
    const uint32_t sfull = sb + B_SFULL + wg * 16, sempty = sb + B_SEMPTY + wg * 16;
    auto drain = [&](float (&S)[32], int b, uint32_t ph, int g, int q) {
      if (g == 0 && q == 3) mbar_wait(sempty + 8 * b, ph);
      if (g >= 1 && g <= 4) stage(S, b, 2 * (g - 1) + (q >> 1), q & 1);
      if (g == 5 && q == 3) { fence_async_smem(); __syncwarp(); if (lane == 0) mbar_arrive(sfull + 8 * b); }
    };
#pragma unroll 1
    for (int it = 0; it < 4; it++) {
      pass(U, G, false, 0, false, [&](int g, int q) { drain(G, 0, (it & 1) ^ 1, g, q); });
      pass(G, U, false, 1, it == 3, [&](int g, int q) { drain(U, 1, (it & 1) ^ 1, g, q); });
    }
    mbar_wait(sempty, 1);
    wg_wait<0>();
    pin(G);
    if (t128 == 0) TSTAMP(14 + wg * 16);
#pragma unroll
    for (int j = 0; j < 16; j++) stage(G, 0, j >> 1, j & 1);
    fence_async_smem(); __syncwarp();
    if (lane == 0) mbar_arrive(sfull);
  }
}

typedef CUresult (*EncodeTiledFn)(CUtensorMap*, CUtensorMapDataType, cuuint32_t, void*, const cuuint64_t*, const cuuint64_t*,
                                  const cuuint32_t*, const cuuint32_t*, CUtensorMapInterleave, CUtensorMapSwizzle,
                                  CUtensorMapL2promotion, CUtensorMapFloatOOBfill);

static void make_map(EncodeTiledFn enc, CUtensorMap* m, const void* ptr, bool f32, uint64_t inner, uint64_t outer,
                     uint32_t bi, uint32_t bo, bool swz) {
  cuuint64_t dims[2] = {inner, outer};
  cuuint64_t strides[1] = {inner * (f32 ? 4u : 2u)};
  cuuint32_t box[2] = {bi, bo}, es[2] = {1, 1};
  enc(m, f32 ? CU_TENSOR_MAP_DATA_TYPE_FLOAT32 : CU_TENSOR_MAP_DATA_TYPE_BFLOAT16, 2, const_cast<void*>(ptr), dims, strides, box, es,
      CU_TENSOR_MAP_INTERLEAVE_NONE, swz ? CU_TENSOR_MAP_SWIZZLE_128B : CU_TENSOR_MAP_SWIZZLE_NONE,
      CU_TENSOR_MAP_L2_PROMOTION_L2_128B, CU_TENSOR_MAP_FLOAT_OOB_FILL_NONE);
}

extern "C" void kernel_launch(void* const* d_in, const int* in_sizes, int n_in, void* d_out, int out_size) {
  (void)in_sizes; (void)n_in; (void)out_size;
  static EncodeTiledFn enc = nullptr;
  if (!enc) {
    void* fn = nullptr; cudaDriverEntryPointQueryResult st;
    cudaGetDriverEntryPoint("cuTensorMapEncodeTiled", &fn, cudaEnableDefault, &st);
    enc = (EncodeTiledFn)fn;
    cudaFuncSetAttribute(fused_s5_swiglu_kernel, cudaFuncAttributeMaxDynamicSharedMemorySize, SMEM_BYTES);
  }
  Params P;
  make_map(enc, &P.mx, d_in[0], false, D_, L_, 64, 64, true);
  make_map(enc, &P.mw1, d_in[10], false, F_, D_, 64, 32, true);
  make_map(enc, &P.mw3, d_in[11], false, F_, D_, 64, 32, true);
  make_map(enc, &P.mw2, d_in[12], false, D_, F_, 64, 32, true);
  make_map(enc, &P.mbre, d_in[3], false, D_, D_, 64, 24, true);
  make_map(enc, &P.mbim, d_in[4], false, D_, D_, 64, 24, true);
  make_map(enc, &P.mcre, d_in[5], false, D_, D_, 64, 32, true);
  make_map(enc, &P.mcim, d_in[6], false, D_, D_, 64, 32, true);
  make_map(enc, &P.mcre8, d_in[5], false, D_, D_, 8, 64, false);
  make_map(enc, &P.mcim8, d_in[6], false, D_, D_, 8, 64, false);
  {
    cuuint64_t dims[4] = {D_, 2, 4, L_ / 8}, strides[3] = {4 * D_ * 4, D_ * 4, 8 * D_ * 4};
    cuuint32_t box[4] = {32, 2, 4, 2}, es[4] = {1, 1, 1, 1};
    enc(&P.mout, CU_TENSOR_MAP_DATA_TYPE_FLOAT32, 4, d_out, dims, strides, box, es, CU_TENSOR_MAP_INTERLEAVE_NONE,
        CU_TENSOR_MAP_SWIZZLE_128B, CU_TENSOR_MAP_L2_PROMOTION_L2_128B, CU_TENSOR_MAP_FLOAT_OOB_FILL_NONE);
  }
  P.x = (const __nv_bfloat16*)d_in[0];
  P.lre = (const __nv_bfloat16*)d_in[1];
  P.lim = (const __nv_bfloat16*)d_in[2];
  P.logdt = (const __nv_bfloat16*)d_in[7];
  P.dskip = (const __nv_bfloat16*)d_in[8];
  P.out = (float*)d_out;
  fused_s5_swiglu_kernel<<<128, 384, SMEM_BYTES, cudaStreamPerThread>>>(P);
}
```

```cpp
#include <cuda_runtime.h>
#include <cuda.h>
#include <cuda_bf16.h>
#include <stdint.h>

#define X_NRED 8
#define MAPPING 1
#define FENCE_ALL 1
#define USE_TANH 1
#define STAGE_FAST 1
#define X_NINIT 24
#define CARRY_DELAY 1000
#define X_PFX 1
#define X_PFB 1
#define X_PFM 1
#define RED_DEPTH 3
#define WAIT_HINT 4000
#define HWAIT mbar_wait
#define PWAIT mbar_wait
#define LAG 3
#define SERIAL 11
#define XDUMMY 1
#define CONS_REGS 240
#define AUX_REGS 24
#define SLICE(bx) (MAPPING ? (bx) >> 4 : ((bx) >> 1) & 7)
#define PAIR(bx) (MAPPING ? ((bx) >> 1) & 7 : (bx) >> 4)
#define STR2(x) #x
#define STR(x) STR2(x)

namespace {

constexpr int L_ = 2048, D_ = 576, F_ = 4608;
constexpr int NSLOT = 6;
constexpr int NBAR = 12;
constexpr int SLOT_B = 8192;
constexpr uint32_t OFF_PARK = 0;
constexpr uint32_t OFF_H = 131072;
constexpr uint32_t OFF_XSLOT = 147456;
constexpr uint32_t OFF_RING = 167936;
constexpr uint32_t OFF_BAR = OFF_RING + NSLOT * SLOT_B;
constexpr uint32_t B_FULL = OFF_BAR, B_EMPTY = B_FULL + 8 * NBAR, B_XFULL = B_EMPTY + 8 * NBAR, B_XDONE = B_XFULL + 8 * 9,
                   B_URDY = B_XDONE + 8, B_HRDY = B_URDY + 8, B_UFREE = B_HRDY + 8, B_SFULL = B_UFREE + 8, B_SEMPTY = B_SFULL + 32, B_CARRY = B_SEMPTY + 32,
                   B_XROW = B_CARRY + 24, B_IDONE = B_XROW + 8, B_END = B_IDONE + 8;
constexpr uint32_t OFF_U0 = OFF_BAR + 1024;
constexpr uint32_t OFF_U = 65536 - 8 * 1024;
constexpr uint32_t OFF_STAT = OFF_BAR + 512, OFF_COEF = OFF_U0 + 8192;
constexpr uint32_t OFF_XROW = 65536 - 17 * 1152;
constexpr uint32_t OFF_REM = (OFF_COEF + 72 * 8 + 127) & ~127u;
constexpr uint32_t OFF_TIM = OFF_REM + 2048;
constexpr uint32_t SMEM_BYTES = OFF_TIM;
static_assert(B_END <= OFF_STAT && OFF_U0 % 1024 == 0 && OFF_XROW % 16 == 0 && SMEM_BYTES <= 232448, "smem map");
constexpr uint32_t SB_LO = 1024;
constexpr uint32_t DESC0 = (SB_LO >> 4) | (1u << 16);
constexpr uint32_t DHI_SW128 = 0x40000040u;
constexpr uint32_t DHI_NOSW = 0x00000008u;
constexpr uint32_t DHI_HT = 0x00000008u;

struct Params {
  CUtensorMap mx, mw1, mw3, mw2, mbre, mbim, mcre, mcim, mcre8, mcim8, mout;
  const __nv_bfloat16 *x, *lre, *lim, *logdt, *dskip;
  float* out;
};

__device__ unsigned long long g_done;
__device__ unsigned int g_initcnt[16];
__device__ uint4 g_E[8 * 3 * 16 * 24];
#define TSTAMP(i)
#define TRC(p)
#define TRP(a)

__device__ __forceinline__ long long gtime() { long long t; asm volatile("mov.u64 %0, %%globaltimer;" : "=l"(t)); return t; }
__device__ __forceinline__ uint32_t smem_u32(const void* p) { return (uint32_t)__cvta_generic_to_shared(p); }
__device__ __forceinline__ void mbar_init(uint32_t bar, uint32_t cnt) { asm volatile("mbarrier.init.shared::cta.b64 [%0], %1;" :: "r"(bar), "r"(cnt) : "memory"); }
__device__ __forceinline__ void mbar_expect_tx(uint32_t bar, uint32_t bytes) { asm volatile("mbarrier.arrive.expect_tx.shared::cta.b64 _, [%0], %1;" :: "r"(bar), "r"(bytes) : "memory"); }
__device__ __forceinline__ void mbar_arrive(uint32_t bar) { asm volatile("mbarrier.arrive.shared::cta.b64 _, [%0];" :: "r"(bar) : "memory"); }
__device__ __forceinline__ void mbar_arrive_rem(uint32_t cbar) { asm volatile("mbarrier.arrive.shared::cluster.b64 _, [%0];" :: "r"(cbar) : "memory"); }
__device__ __forceinline__ void mbar_wait(uint32_t bar, uint32_t parity) {
  asm volatile("{\n.reg .pred p;\n.reg .u32 c;\n"
    "mbarrier.try_wait.parity.shared::cta.b64 p, [%0], %1;\n@p bra LAB_DONE;\nmov.u32 c, 0;\n"
    "LAB_WAIT:\nmbarrier.try_wait.parity.shared::cta.b64 p, [%0], %1;\n@p bra LAB_DONE;\n"
    "add.u32 c, c, 1;\nsetp.lt.u32 p, c, 2000000;\n@p bra LAB_WAIT;\ntrap;\nLAB_DONE:\n}" :: "r"(bar), "r"(parity) : "memory");
}
__device__ __forceinline__ void mbar_wait_long(uint32_t bar, uint32_t parity) {
  asm volatile("{\n.reg .pred p;\n.reg .u32 c;\nmov.u32 c, 0;\n"
    "LAB_WAIT:\nmbarrier.try_wait.parity.shared::cta.b64 p, [%0], %1, %2;\n@p bra LAB_DONE;\n"
    "add.u32 c, c, 1;\nsetp.lt.u32 p, c, 2000000;\n@p bra LAB_WAIT;\ntrap;\nLAB_DONE:\n}" :: "r"(bar), "r"(parity), "r"(WAIT_HINT) : "memory");
}
__device__ __forceinline__ void mbar_probe(uint32_t bar, uint32_t parity) {
  asm volatile("mbarrier.test_wait.parity.shared::cta.b64 PROBE, [%0], %1;" :: "r"(bar), "r"(parity) : "memory");
}
__device__ __forceinline__ void mbar_finish(uint32_t bar, uint32_t parity) {
  asm volatile("{\n.reg .u32 c;\n@PROBE bra LAB_DONE;\nmov.u32 c, 0;\n"
    "LAB_WAIT:\nmbarrier.try_wait.parity.shared::cta.b64 PROBE, [%0], %1;\n@PROBE bra LAB_DONE;\n"
    "add.u32 c, c, 1;\nsetp.lt.u32 PROBE, c, 2000000;\n@PROBE bra LAB_WAIT;\ntrap;\nLAB_DONE:\n}" :: "r"(bar), "r"(parity) : "memory");
}
__device__ __forceinline__ void flag_wait(const unsigned int* p, unsigned int v) {
  asm volatile("{\n.reg .pred q;\n.reg .u32 c, t;\nmov.u32 c, 0;\n"
    "LAB_WAIT:\nld.acquire.gpu.global.u32 t, [%0];\nsetp.eq.u32 q, t, %1;\n@q bra LAB_DONE;\n"
    "nanosleep.u32 64;\nadd.u32 c, c, 1;\nsetp.lt.u32 q, c, 4000000;\n@q bra LAB_WAIT;\ntrap;\nLAB_DONE:\n}" :: "l"(p), "r"(v) : "memory");
}
__device__ __forceinline__ void tma_load(uint32_t dst, const CUtensorMap* m, uint32_t bar, int c0, int c1) {
  asm volatile("cp.async.bulk.tensor.2d.shared::cluster.global.mbarrier::complete_tx::bytes [%0], [%1, {%3, %4}], [%2];"
    :: "r"(dst), "l"(m), "r"(bar), "r"(c0), "r"(c1) : "memory");
}
__device__ __forceinline__ void tma_load_mc(uint32_t dst, const CUtensorMap* m, uint32_t bar, int c0, int c1) {
  asm volatile("cp.async.bulk.tensor.2d.shared::cluster.global.mbarrier::complete_tx::bytes.multicast::cluster [%0], [%1, {%3, %4}], [%2], %5;"
    :: "r"(dst), "l"(m), "r"(bar), "r"(c0), "r"(c1), "h"((uint16_t)3) : "memory");
}
__device__ __forceinline__ void tma_prefetch(const CUtensorMap* m, int c0, int c1) {
  asm volatile("cp.async.bulk.prefetch.tensor.2d.L2.global [%0, {%1, %2}];" :: "l"(m), "r"(c0), "r"(c1) : "memory");
}
__device__ __forceinline__ int fresh_ctaid() { int r; asm volatile("mov.u32 %0, %%ctaid.x;" : "=r"(r)); return r; }
__device__ __forceinline__ bool elect() {
  uint32_t r; asm volatile("{\n.reg .pred p;\nelect.sync _|p, 0xffffffff;\nselp.u32 %0, 1, 0, p;\n}" : "=r"(r)); return r;
}
__device__ __forceinline__ void wg_fence() { asm volatile("wgmma.fence.sync.aligned;" ::: "memory"); }
__device__ __forceinline__ void wg_commit() { asm volatile("wgmma.commit_group.sync.aligned;" ::: "memory"); }
template<int N> __device__ __forceinline__ void wg_wait() { asm volatile("wgmma.wait_group.sync.aligned %0;" :: "n"(N) : "memory"); }
__device__ __forceinline__ void fence_async_smem() { asm volatile("fence.proxy.async.shared::cta;" ::: "memory"); }
__device__ __forceinline__ uint64_t mkdesc(uint32_t lo, uint32_t hi) { return ((uint64_t)hi << 32) | lo; }
template<int N> __device__ __forceinline__ void pin(float (&d)[N]) {
#pragma unroll
  for (int i = 0; i < N; i++) asm volatile("" : "+f"(d[i]) :: "memory");
}
__device__ __forceinline__ uint32_t pack_bf16(float lo, float hi) { uint32_t r; asm("cvt.rn.bf16x2.f32 %0, %1, %2;" : "=r"(r) : "f"(hi), "f"(lo)); return r; }
__device__ __forceinline__ float bf_round(float v) { return __bfloat162float(__float2bfloat16_rn(v)); }
__device__ __forceinline__ float bf_lo(uint32_t v) { return __uint_as_float(v << 16); }
__device__ __forceinline__ float bf_hi(uint32_t v) { return __uint_as_float(v & 0xffff0000u); }
__device__ __forceinline__ uint32_t hmul2_bf16(uint32_t a, uint32_t b) { uint32_t r; asm("mul.rn.bf16x2 %0, %1, %2;" : "=r"(r) : "r"(a), "r"(b)); return r; }
__device__ __forceinline__ uint32_t hsub2_bf16(uint32_t a, uint32_t b) { uint32_t r; asm("sub.rn.bf16x2 %0, %1, %2;" : "=r"(r) : "r"(a), "r"(b)); return r; }
__device__ __forceinline__ void sts64(uint32_t a, uint32_t x, uint32_t y) { asm volatile("st.shared.v2.b32 [%0], {%1, %2};" :: "r"(a), "r"(x), "r"(y) : "memory"); }
__device__ __forceinline__ void sts64f(uint32_t a, float x, float y) { asm volatile("st.shared.v2.f32 [%0], {%1, %2};" :: "r"(a), "f"(x), "f"(y) : "memory"); }
__device__ __forceinline__ void sts128(uint32_t a, const uint32_t* v) { asm volatile("st.shared.v4.b32 [%0], {%1, %2, %3, %4};" :: "r"(a), "r"(v[0]), "r"(v[1]), "r"(v[2]), "r"(v[3]) : "memory"); }
__device__ __forceinline__ void lds128(uint32_t* v, uint32_t a) { asm volatile("ld.shared.v4.b32 {%0, %1, %2, %3}, [%4];" : "=r"(v[0]), "=r"(v[1]), "=r"(v[2]), "=r"(v[3]) : "r"(a) : "memory"); }
__device__ __forceinline__ void sts32f(uint32_t a, float x) { asm volatile("st.shared.f32 [%0], %1;" :: "r"(a), "f"(x) : "memory"); }
__device__ __forceinline__ void lds128f(float* v, uint32_t a) { asm volatile("ld.shared.v4.f32 {%0, %1, %2, %3}, [%4];" : "=f"(v[0]), "=f"(v[1]), "=f"(v[2]), "=f"(v[3]) : "r"(a) : "memory"); }

__device__ __forceinline__ void mma16816(float (&d)[4], const uint32_t* a, uint32_t b0, uint32_t b1) {
  asm volatile("mma.sync.aligned.m16n8k16.row.col.f32.bf16.bf16.f32 {%0, %1, %2, %3}, {%4, %5, %6, %7}, {%8, %9}, {%0, %1, %2, %3};"
    : "+f"(d[0]), "+f"(d[1]), "+f"(d[2]), "+f"(d[3]) : "r"(a[0]), "r"(a[1]), "r"(a[2]), "r"(a[3]), "r"(b0), "r"(b1));
}
__device__ __forceinline__ float std_of(float var) { float q; asm("sqrt.approx.ftz.f32 %0, %1;" : "=f"(q) : "f"(bf_round(bf_round(var) + 1e-5f))); return q; }
__device__ __forceinline__ float rcp_bf(float q) { float r; asm("rcp.approx.ftz.f32 %0, %1;" : "=f"(r) : "f"(bf_round(q))); return r; }

template<int TB> __device__ __forceinline__ void wg_rs48(float (&d)[24], const uint32_t* a, uint64_t db) {
  asm volatile("{\n.reg .pred p;\nsetp.ne.b32 p, 1, 0;\n"
  "wgmma.mma_async.sync.aligned.m64n48k16.f32.bf16.bf16 "
  "{%0, %1, %2, %3, %4, %5, %6, %7, %8, %9, %10, %11, %12, %13, %14, %15, %16, %17, %18, %19, %20, %21, %22, %23}, "
  "{%24, %25, %26, %27}, %28, p, 1, 1, %29;\n}\n"
  : "+f"(d[0]), "+f"(d[1]), "+f"(d[2]), "+f"(d[3]), "+f"(d[4]), "+f"(d[5]), "+f"(d[6]), "+f"(d[7]),
    "+f"(d[8]), "+f"(d[9]), "+f"(d[10]), "+f"(d[11]), "+f"(d[12]), "+f"(d[13]), "+f"(d[14]), "+f"(d[15]),
    "+f"(d[16]), "+f"(d[17]), "+f"(d[18]), "+f"(d[19]), "+f"(d[20]), "+f"(d[21]), "+f"(d[22]), "+f"(d[23])
  : "r"(a[0]), "r"(a[1]), "r"(a[2]), "r"(a[3]), "l"(db), "n"(TB));
}
template<int TB> __device__ __forceinline__ void wg_rs48_z(float (&d)[24], const uint32_t* a, uint64_t db) {
  asm volatile("{\n.reg .pred p;\nsetp.ne.b32 p, 0, 0;\n"
  "wgmma.mma_async.sync.aligned.m64n48k16.f32.bf16.bf16 "
  "{%0, %1, %2, %3, %4, %5, %6, %7, %8, %9, %10, %11, %12, %13, %14, %15, %16, %17, %18, %19, %20, %21, %22, %23}, "
  "{%24, %25, %26, %27}, %28, p, 1, 1, %29;\n}\n"
  : "=f"(d[0]), "=f"(d[1]), "=f"(d[2]), "=f"(d[3]), "=f"(d[4]), "=f"(d[5]), "=f"(d[6]), "=f"(d[7]),
    "=f"(d[8]), "=f"(d[9]), "=f"(d[10]), "=f"(d[11]), "=f"(d[12]), "=f"(d[13]), "=f"(d[14]), "=f"(d[15]),
    "=f"(d[16]), "=f"(d[17]), "=f"(d[18]), "=f"(d[19]), "=f"(d[20]), "=f"(d[21]), "=f"(d[22]), "=f"(d[23])
  : "r"(a[0]), "r"(a[1]), "r"(a[2]), "r"(a[3]), "l"(db), "n"(TB));
}
template<int TB> __device__ __forceinline__ void wg_rs64(float (&d)[32], const uint32_t* a, uint64_t db) {
  asm volatile("{\n.reg .pred p;\nsetp.ne.b32 p, 1, 0;\n"
  "wgmma.mma_async.sync.aligned.m64n64k16.f32.bf16.bf16 "
  "{%0, %1, %2, %3, %4, %5, %6, %7, %8, %9, %10, %11, %12, %13, %14, %15, %16, %17, %18, %19, %20, %21, %22, %23, %24, %25, %26, %27, %28, %29, %30, %31}, "
  "{%32, %33, %34, %35}, %36, p, 1, 1, %37;\n}\n"
  : "+f"(d[0]), "+f"(d[1]), "+f"(d[2]), "+f"(d[3]), "+f"(d[4]), "+f"(d[5]), "+f"(d[6]), "+f"(d[7]),
    "+f"(d[8]), "+f"(d[9]), "+f"(d[10]), "+f"(d[11]), "+f"(d[12]), "+f"(d[13]), "+f"(d[14]), "+f"(d[15]),
    "+f"(d[16]), "+f"(d[17]), "+f"(d[18]), "+f"(d[19]), "+f"(d[20]), "+f"(d[21]), "+f"(d[22]), "+f"(d[23]),
    "+f"(d[24]), "+f"(d[25]), "+f"(d[26]), "+f"(d[27]), "+f"(d[28]), "+f"(d[29]), "+f"(d[30]), "+f"(d[31])
  : "r"(a[0]), "r"(a[1]), "r"(a[2]), "r"(a[3]), "l"(db), "n"(TB));
}
template<int TB> __device__ __forceinline__ void wg_rs64_z(float (&d)[32], const uint32_t* a, uint64_t db) {
  asm volatile("{\n.reg .pred p;\nsetp.ne.b32 p, 0, 0;\n"
  "wgmma.mma_async.sync.aligned.m64n64k16.f32.bf16.bf16 "
  "{%0, %1, %2, %3, %4, %5, %6, %7, %8, %9, %10, %11, %12, %13, %14, %15, %16, %17, %18, %19, %20, %21, %22, %23, %24, %25, %26, %27, %28, %29, %30, %31}, "
  "{%32, %33, %34, %35}, %36, p, 1, 1, %37;\n}\n"
  : "=f"(d[0]), "=f"(d[1]), "=f"(d[2]), "=f"(d[3]), "=f"(d[4]), "=f"(d[5]), "=f"(d[6]), "=f"(d[7]),
    "=f"(d[8]), "=f"(d[9]), "=f"(d[10]), "=f"(d[11]), "=f"(d[12]), "=f"(d[13]), "=f"(d[14]), "=f"(d[15]),
    "=f"(d[16]), "=f"(d[17]), "=f"(d[18]), "=f"(d[19]), "=f"(d[20]), "=f"(d[21]), "=f"(d[22]), "=f"(d[23]),
    "=f"(d[24]), "=f"(d[25]), "=f"(d[26]), "=f"(d[27]), "=f"(d[28]), "=f"(d[29]), "=f"(d[30]), "=f"(d[31])
  : "r"(a[0]), "r"(a[1]), "r"(a[2]), "r"(a[3]), "l"(db), "n"(TB));
}
template<int TA, int TB> __device__ __forceinline__ void wg_ss64(float (&d)[32], uint64_t da, uint64_t db) {
  asm volatile("{\n.reg .pred p;\nsetp.ne.b32 p, 1, 0;\n"
  "wgmma.mma_async.sync.aligned.m64n64k16.f32.bf16.bf16 "
  "{%0, %1, %2, %3, %4, %5, %6, %7, %8, %9, %10, %11, %12, %13, %14, %15, %16, %17, %18, %19, %20, %21, %22, %23, %24, %25, %26, %27, %28, %29, %30, %31}, "
  "%32, %33, p, 1, 1, %35, %34;\n}\n"
  : "+f"(d[0]), "+f"(d[1]), "+f"(d[2]), "+f"(d[3]), "+f"(d[4]), "+f"(d[5]), "+f"(d[6]), "+f"(d[7]),
    "+f"(d[8]), "+f"(d[9]), "+f"(d[10]), "+f"(d[11]), "+f"(d[12]), "+f"(d[13]), "+f"(d[14]), "+f"(d[15]),
    "+f"(d[16]), "+f"(d[17]), "+f"(d[18]), "+f"(d[19]), "+f"(d[20]), "+f"(d[21]), "+f"(d[22]), "+f"(d[23]),
    "+f"(d[24]), "+f"(d[25]), "+f"(d[26]), "+f"(d[27]), "+f"(d[28]), "+f"(d[29]), "+f"(d[30]), "+f"(d[31])
  : "l"(da), "l"(db), "n"(TB), "n"(TA));
}
template<int TA, int TB> __device__ __forceinline__ void wg_ss64_z(float (&d)[32], uint64_t da, uint64_t db) {
  asm volatile("{\n.reg .pred p;\nsetp.ne.b32 p, 0, 0;\n"
  "wgmma.mma_async.sync.aligned.m64n64k16.f32.bf16.bf16 "
  "{%0, %1, %2, %3, %4, %5, %6, %7, %8, %9, %10, %11, %12, %13, %14, %15, %16, %17, %18, %19, %20, %21, %22, %23, %24, %25, %26, %27, %28, %29, %30, %31}, "
  "%32, %33, p, 1, 1, %35, %34;\n}\n"
  : "=f"(d[0]), "=f"(d[1]), "=f"(d[2]), "=f"(d[3]), "=f"(d[4]), "=f"(d[5]), "=f"(d[6]), "=f"(d[7]),
    "=f"(d[8]), "=f"(d[9]), "=f"(d[10]), "=f"(d[11]), "=f"(d[12]), "=f"(d[13]), "=f"(d[14]), "=f"(d[15]),
    "=f"(d[16]), "=f"(d[17]), "=f"(d[18]), "=f"(d[19]), "=f"(d[20]), "=f"(d[21]), "=f"(d[22]), "=f"(d[23]),
    "=f"(d[24]), "=f"(d[25]), "=f"(d[26]), "=f"(d[27]), "=f"(d[28]), "=f"(d[29]), "=f"(d[30]), "=f"(d[31])
  : "l"(da), "l"(db), "n"(TB), "n"(TA));
}

__host__ __device__ constexpr uint32_t slot_off(int b) { return b < NSLOT ? OFF_RING + b * SLOT_B : b == NSLOT ? OFF_U0 : OFF_PARK + (b - 7) * (LAG ? 16384 : SLOT_B); }

struct Pipe {
  uint32_t full, rel;
  bool sig;
  __device__ __forceinline__ void wait(int b, uint32_t ph) { mbar_wait(full + 8 * b, ph); }
  __device__ __forceinline__ void probe(int b, uint32_t ph) { mbar_probe(full + 8 * b, ph); }
  __device__ __forceinline__ void finish(int b, uint32_t ph) { mbar_finish(full + 8 * b, ph); }
  static __device__ __forceinline__ constexpr uint32_t desc(int b) { return DESC0 + (slot_off(b) >> 4); }
  __device__ __forceinline__ void release(int b) {
    if (sig) {
      mbar_arrive_rem(rel + 8 * b);
    }
  }
};

template<int N, int S0, int PREV, bool AMOD = false, class PieceF, class DoneF>
__device__ __forceinline__ void kloop(float (&acc)[N / 2], const uint32_t (&A)[144], Pipe& p, uint32_t ph, PieceF piece, DoneF done0) {
#pragma unroll
  for (int kk = 0; kk < 9; kk++) {
    const int nb = N == 64 ? (S0 + kk + 1) % NSLOT : (kk + 1) % 9;
    const uint32_t nph = ph ^ (N == 64 ? ((S0 + kk + 1) / NSLOT) & 1 : kk == 8);
    p.probe(nb, nph);
    if (FENCE_ALL || AMOD || kk == 0) wg_fence();
#pragma unroll
    for (int q = 0; q < 4; q++) {
      if constexpr (N == 64) {
        const uint64_t db = mkdesc(p.desc((S0 + kk) % NSLOT) + q * 128, DHI_SW128);
        if (kk == 0 && q == 0) wg_rs64_z<1>(acc, &A[0], db); else wg_rs64<1>(acc, &A[kk * 16 + q * 4], db);
      } else {
        const uint64_t db = mkdesc((kk < NSLOT ? p.desc(kk) : DESC0 + ((OFF_XSLOT + (kk - NSLOT) * 6144) >> 4)) + q * 2, DHI_SW128);
        if (kk == 0 && q == 0) wg_rs48_z<0>(acc, &A[0], db); else wg_rs48<0>(acc, &A[kk * 16 + q * 4], db);
      }
      if (q == 3) wg_commit();
      piece(kk, q);
    }
    const int prev = kk == 0 ? PREV : N == 64 ? (S0 + kk - 1) % NSLOT : (S0 == 2 && kk > NSLOT) ? -2 : kk - 1;
    if (prev != -1) wg_wait<1>();
    if (prev >= 0) p.release(prev);
    p.finish(nb, nph);
    TRC(p);
    if (kk == 0) done0();
  }
}

}

__global__ void __cluster_dims__(2, 1, 1) __launch_bounds__(384, 1) fused_s5_swiglu_kernel(const __grid_constant__ Params P) {
  extern __shared__ __align__(1024) uint8_t smem_raw[];
  asm volatile(".reg .pred PROBE;");
  const uint32_t sb = smem_u32(smem_raw);
  if ((sb & 0xFFFFFFu) != SB_LO) asm volatile("trap;");
  const int tid = threadIdx.x;
  const int wg = __shfl_sync(0xffffffff, tid >> 7, 0);
  const int rank = blockIdx.x & 1;
  const int cl = blockIdx.x >> 1;
  const int sl = MAPPING ? cl >> 3 : cl & 7, mp = MAPPING ? cl & 7 : cl >> 3;
  const int mb = mp * 2 + rank;

  if (tid == 256) {
    TSTAMP(0);
#pragma unroll
    for (int i = 0; i < 9; i++) mbar_init(sb + B_XFULL + 8 * i, 1);
    asm volatile("fence.mbarrier_init.release.cluster;" ::: "memory");
  } else if (tid == 288) {
#pragma unroll
    for (int i = 0; i < NBAR; i++) { mbar_init(sb + B_FULL + 8 * i, 1); mbar_init(sb + B_EMPTY + 8 * i, 4); }
    asm volatile("fence.mbarrier_init.release.cluster;" ::: "memory");
  } else if (tid == 320) {
#pragma unroll
    for (int i = 0; i < 4; i++) { mbar_init(sb + B_SFULL + 8 * i, 4); mbar_init(sb + B_SEMPTY + 8 * i, 1); }
#pragma unroll
    for (int i = 0; i < 3; i++) mbar_init(sb + B_CARRY + 8 * i, 1);
    mbar_init(sb + B_XDONE, 11); mbar_init(sb + B_URDY, 8); mbar_init(sb + B_HRDY, 3); mbar_init(sb + B_UFREE, 3);
    mbar_init(sb + B_XROW, 2); mbar_init(sb + B_IDONE, 3);
    asm volatile("fence.mbarrier_init.release.cluster;" ::: "memory");
  }
  __syncwarp();
  asm volatile("barrier.cluster.arrive.relaxed.aligned;" ::: "memory");
  if (tid >= 256 && tid < 288) {
    if (elect()) {
#pragma unroll 1
      for (int i = 0; i < 9; i++) {
        mbar_expect_tx(sb + B_XFULL + 8 * i, 16384);
        tma_load(sb + i * 16384, &P.mx, sb + B_XFULL + 8 * i, i * 64, mb * 128);
      }
    }
    __syncwarp();
  }
  asm volatile("barrier.cluster.wait.acquire.aligned;" ::: "memory");

  if (tid == 0) TSTAMP(56);
  if (wg == 2) {
    asm volatile("setmaxnreg.dec.sync.aligned.u32 " STR(AUX_REGS) ";");
    const int warp = __shfl_sync(0xffffffff, (tid >> 5) & 3, 0), lane = tid & 31;
    if (warp == 0) {
      if (elect()) {
        const uint32_t full = sb + B_FULL, empty = sb + B_EMPTY;
        auto put = [&](int b, uint32_t dst, uint32_t ph, const CUtensorMap* m, uint32_t bytes, int c0, int c1) {
          PWAIT(empty + 8 * b, ph);
          mbar_expect_tx(full + 8 * b, bytes);
          tma_load_mc(dst, m, full + 8 * b, c0, c1);
          TRP(trp);
        };
        {
          const int bx = fresh_ctaid(), rk = bx & 1;
          const CUtensorMap* m = &P.mbre + rk;
          const uint32_t d = sb + rk * 3072;
          int c1 = SLICE(bx) * 72;
#pragma unroll 1
          for (int t = 0; t < 3; t++, c1 += 24) {
#pragma unroll
            for (int kk = 0; kk < 9; kk++) put(kk, d + (kk < 6 ? OFF_RING + kk * SLOT_B : OFF_XSLOT + (kk - 6) * 6144), (t & 1) ^ 1, m, 6144, kk * 64, c1);
            if (t == 0) {
              const int pr = PAIR(bx);
              tma_prefetch(m, pr * 64, c1 + 24); tma_prefetch(m, pr * 64, c1 + 48);
              if (pr < 2) tma_prefetch(m, 512, c1 + 24 + pr * 24);
            }
          }
        }
        {
          const int bx = fresh_ctaid(), rk = bx & 1;
          const uint32_t d = sb + OFF_RING + rk * 4096;
          int c0 = SLICE(bx) * 576;
#pragma unroll 1
          for (int j = 0; j < 9; j++, c0 += 64) {
#pragma unroll
            for (int n = 0; n < 18; n++)
              put(n % 6, d + (n % 6) * SLOT_B, (j + n / 6) & 1, n < 9 ? &P.mw1 : &P.mw3, 8192, c0, (n % 9) * 64 + rk * 32);
          }
        }
        {
          const int bx = fresh_ctaid(), rk = bx & 1, s = SLICE(bx);
          const uint32_t d = sb + rk * 4096;
          int n0 = s * 64;
          put(11, sb + rk * 1024 + OFF_REM, 1, &P.mcre8 + rk, 2048, s * 72 + 64, n0);
          put(0, d + slot_off(0), 1, &P.mcre, 8192, s * 72, n0 + rk * 32);
          put(1, d + slot_off(1), 1, &P.mcim, 8192, s * 72, n0 + rk * 32);
#pragma unroll
          for (int kk = 0; kk < 9; kk++) put(kk + 2, d + slot_off(kk + 2), kk < 4, &P.mw2, 8192, n0, s * 576 + rk * 32 + kk * 64);
#pragma unroll 1
          for (int p = 1; p < 9; p++) {
            n0 = n0 == 512 ? 0 : n0 + 64;
            const uint32_t hi = p & 1;
#pragma unroll
            for (int kk = 0; kk < 9; kk++) put(kk, d + slot_off(kk), kk < 6 ? hi ^ 1 : hi, &P.mw2, 8192, n0, s * 576 + rk * 32 + kk * 64);
            put(9, d + slot_off(9), hi, &P.mcre, 8192, s * 72, n0 + rk * 32);
            put(10, d + slot_off(10), hi, &P.mcim, 8192, s * 72, n0 + rk * 32);
            put(11, sb + rk * 1024 + OFF_REM, hi ^ 1, &P.mcre8 + rk, 2048, s * 72 + 64, n0);
          }
        }
      }
    } else {
      const int w = warp - 1;
      const int ls = lane < 24 ? lane : 0;
      float lr, li;
        {
          const int pg = sl * 72 + w * 24 + ls;
          const float dt = bf_round(expf(__bfloat162float(P.logdt[pg])));
          const float ar = __bfloat162float(P.lre[pg]), ai = __bfloat162float(P.lim[pg]);
          const float e = expf(dt * ar);
          float sn, cs; sincosf(dt * ai, &sn, &cs);
          lr = e * cs; li = e * sn;
          const float inv = 2.0f / (ar * ar + ai * ai);
          sts64f(sb + OFF_COEF + (w * 24 + ls) * 8, ((lr - 1.0f) * ar + li * ai) * inv, (li * ar - (lr - 1.0f) * ai) * inv);
          __syncwarp();
          if (lane == 0) mbar_arrive(sb + B_XDONE);
        }
      uint32_t epoch;
      { unsigned long long dn; asm volatile("ld.relaxed.gpu.global.u64 %0, [%1];" : "=l"(dn) : "l"(&g_done) : "memory"); epoch = (uint32_t)(dn >> 7) + 1u; }
      auto pf9 = [&](const CUtensorMap* m, int c0, int c1) {
        tma_prefetch(m, c0, c1 + mp * 64 + rank * 32);
        if (mp == w) tma_prefetch(m, c0, c1 + 512 + rank * 32);
      };
      auto pf_mlp = [&](int j) { if (lane == 0) { pf9(&P.mw1, sl * 576 + j * 64, 0); pf9(&P.mw3, sl * 576 + j * 64, 0); } };
      auto pf_out = [&]() {
        if (lane == 0) {
#pragma unroll 1
          for (int nb = w; nb < 9; nb += 3) {
            pf9(&P.mw2, nb * 64, sl * 576);
            if (mp == (nb & 7)) {
              tma_prefetch(&P.mcre, sl * 72, nb * 64 + rank * 32);
              tma_prefetch(&P.mcim, sl * 72, nb * 64 + rank * 32);
              tma_prefetch(rank ? &P.mcim8 : &P.mcre8, sl * 72 + 64, nb * 64);
            }
          }
        }
      };
      {
        {
          HWAIT(sb + B_XFULL + 8 * 8, 0);
          pf_mlp(w);
          if (w == 0 && lane == 0) {
            HWAIT(sb + B_XDONE, 0);
            fence_async_smem();
            mbar_expect_tx(sb + B_XROW, 17 * 1152);
            asm volatile("cp.async.bulk.shared::cluster.global.mbarrier::complete_tx::bytes [%0], [%1], %2, [%3];"
              :: "r"(sb + OFF_XROW), "l"(P.x + (size_t)(mb * 128 + sl * 16) * D_), "r"(16 * 1152), "r"(sb + B_XROW) : "memory");
            asm volatile("cp.async.bulk.shared::cluster.global.mbarrier::complete_tx::bytes [%0], [%1], %2, [%3];"
              :: "r"(sb + OFF_XROW + 16 * 1152), "l"(P.dskip), "r"(1152), "r"(sb + B_XROW) : "memory");
          }
          __syncwarp();
          HWAIT(sb + B_XROW, 0);
          float4* op = reinterpret_cast<float4*>(P.out + (size_t)(mb * 128 + sl * 16) * D_) + w * 32 + lane;
          uint32_t xa = sb + OFF_XROW + (w * 32 + lane) * 8, da = xa + 16 * 1152, sa = sb + OFF_STAT;
#pragma unroll 2
          for (int it = 0; it < 24; it++, xa += 768, op += 96) {
            uint32_t v0, v1, k0, k1, m2; float rs;
            asm volatile("ld.shared.v2.b32 {%0, %1}, [%2];" : "=r"(v0), "=r"(v1) : "r"(xa));
            asm volatile("ld.shared.v2.b32 {%0, %1}, [%2];" : "=r"(k0), "=r"(k1) : "r"(da));
            asm volatile("ld.shared.v2.b32 {%0, %1}, [%2];" : "=r"(m2), "=f"(rs) : "r"(sa));
            const uint32_t d0 = hsub2_bf16(v0, m2), d1 = hsub2_bf16(v1, m2);
            const uint32_t t0 = hmul2_bf16(pack_bf16(bf_lo(d0) * rs, bf_hi(d0) * rs), k0);
            const uint32_t t1 = hmul2_bf16(pack_bf16(bf_lo(d1) * rs, bf_hi(d1) * rs), k1);
            *op = make_float4(bf_lo(v0) + bf_lo(t0), bf_hi(v0) + bf_hi(t0), bf_lo(v1) + bf_lo(t1), bf_hi(v1) + bf_hi(t1));
            da += 768; if (da >= sb + OFF_XROW + 17 * 1152) { da -= 1152; sa += 8; }
          }
          __syncwarp();
          if (lane == 0) mbar_arrive(sb + B_IDONE);
          pf_mlp(3 + w);
          if (w == 0 && lane == 0) TSTAMP(49);
        }
        HWAIT(sb + B_URDY, 0);
        if (w == 0 && lane == 0) TSTAMP(40);
        float gr = 0.f, gi = 0.f;
        const uint32_t h0 = sb + OFF_H + (w * 3 + (ls >> 3)) * 2048 + (ls & 7) * 16;
        {
          uint32_t a = (sb + (w * 24 + ls < 8 ? OFF_U0 : OFF_U) + (w * 24 + ls) * 1024) ^ ((ls & 7) << 4), ha = h0;
#pragma unroll 1
          do {
            float v[4][4];
#pragma unroll
            for (int i = 0; i < 4; i++) lds128f(v[i], a ^ (i << 4));
            uint32_t ore[4], oim[4];
#pragma unroll
            for (int i = 0; i < 4; i++) {
              const float r0 = fmaf(lr, gr, fmaf(-li, gi, v[i][0])), i0 = fmaf(lr, gi, fmaf(li, gr, v[i][1]));
              gr = fmaf(lr, r0, fmaf(-li, i0, v[i][2])); gi = fmaf(lr, i0, fmaf(li, r0, v[i][3]));
              ore[i] = pack_bf16(r0, gr); oim[i] = pack_bf16(-i0, -gi);
            }
            if (lane < 24) { sts128(ha, ore); sts128(ha + 9 * 2048, oim); }
            ha += 128;
            a = (a ^ 64) + ((ha & 128) ? 0 : 128);
          } while ((ha & 0x780) != (SB_LO & 0x780));
        }
        uint4* const gE = g_E + (sl * 3 + w) * 16 * 24;
        if (mb < 15 && lane < 24)
          asm volatile("st.relaxed.gpu.global.v2.b64 [%0], {%1, %2};" :: "l"(gE + mb * 24 + lane),
            "l"(((uint64_t)epoch << 32) | __float_as_uint(gr)), "l"(((uint64_t)epoch << 32) | __float_as_uint(gi)) : "memory");
        __syncwarp();
        if (lane == 0) {
          mbar_arrive(sb + B_UFREE);
          asm volatile("red.release.gpu.global.add.u32 [%0], 1;" :: "l"(&g_initcnt[mb]) : "memory");
        }
        pf_mlp(6 + w);
        if (lane == 0) TSTAMP(w ? 56 + w : 46);
        if (mb > 0) {
          HWAIT(sb + B_UFREE, 0);
          __nanosleep(CARRY_DELAY);
          float pr = lr, pi = li;
#pragma unroll
          for (int i = 0; i < 7; i++) { const float t = pr * pr - pi * pi; pi = 2.0f * pr * pi; pr = t; }
          const uint32_t eb = sb + (w < 2 ? OFF_PARK + 7 * 16384 + w * 5760 : OFF_U0);
          uint32_t tries = 0;
          bool ok;
          do {
            if (lane == 0) {
              fence_async_smem();
              mbar_expect_tx(sb + B_CARRY + 8 * w, mb * 384);
              asm volatile("cp.async.bulk.shared::cluster.global.mbarrier::complete_tx::bytes [%0], [%1], %2, [%3];"
                :: "r"(eb), "l"(gE), "r"(mb * 384), "r"(sb + B_CARRY + 8 * w) : "memory");
            }
            HWAIT(sb + B_CARRY + 8 * w, tries & 1);
            gr = 0.f; gi = 0.f;
            uint32_t bad = 0;
#pragma unroll 1
            for (uint32_t a = eb + ls * 16; a < eb + mb * 384; a += 384) {
              uint32_t e[4]; lds128(e, a);
              bad |= (e[1] ^ epoch) | (e[3] ^ epoch);
              const float nr = fmaf(pr, gr, fmaf(-pi, gi, __uint_as_float(e[0])));
              gi = fmaf(pr, gi, fmaf(pi, gr, __uint_as_float(e[2])));
              gr = nr;
            }
            ok = __all_sync(0xffffffff, bad == 0);
            if (!ok) __nanosleep(400);
            if (++tries > 200000) asm volatile("trap;");
          } while (!ok);
          if (lane == 0) TSTAMP(w ? 60 + w : 41);
          if (lane < 24) {
            uint32_t ha = h0;
#pragma unroll 1
            for (int it = 0; it < 16; it++, ha += 128) {
              uint32_t vr[4], vi[4];
              lds128(vr, ha); lds128(vi, ha + 9 * 2048);
#pragma unroll
              for (int i = 0; i < 4; i++) {
                const float r0 = fmaf(lr, gr, -li * gi), i0 = fmaf(lr, gi, li * gr);
                gr = fmaf(lr, r0, -li * i0); gi = fmaf(lr, i0, li * r0);
                vr[i] = pack_bf16(bf_lo(vr[i]) + r0, bf_hi(vr[i]) + gr);
                vi[i] = pack_bf16(bf_lo(vi[i]) - i0, bf_hi(vi[i]) - gi);
              }
              sts128(ha, vr); sts128(ha + 9 * 2048, vi);
            }
          }
        }
        fence_async_smem();
        __syncwarp();
        if (lane == 0) mbar_arrive(sb + B_HRDY);
        pf_out();
        if (lane == 0) TSTAMP(w ? 58 + w : 42);
      }
      if (w < 2 && lane == 0) {
        flag_wait(&g_initcnt[mb], epoch * 24u);
        asm volatile("fence.proxy.async.global;" ::: "memory");
        int nb = sl;
#pragma unroll 1
        for (int p = 0; p < 9; p++) {
          const int b = p & 1;
          HWAIT(sb + B_SFULL + (w * 2 + b) * 8, (p >> 1) & 1);
          if (w == 0 && p >= 5) TSTAMP(32 + (p - 5) * 2);
#pragma unroll 1
          for (int i = 0; i < X_NRED; i++) {
            const uint32_t src = sb + OFF_PARK + (4 + 2 * b + (i >> 2)) * 16384 + w * 8192 + (i & 3) * 2048;
            asm volatile("cp.reduce.async.bulk.tensor.4d.global.shared::cta.add.tile.bulk_group [%0, {%2, %3, %3, %4}], [%1];"
              :: "l"(&P.mout), "r"(src), "r"(nb * 64 + (i >> 2) * 32), "r"(0), "r"(mb * 16 + w * 8 + (i & 3) * 2) : "memory");
            asm volatile("cp.async.bulk.commit_group;" ::: "memory");
            if (p < 8) asm volatile("cp.async.bulk.wait_group.read " STR(RED_DEPTH) ";" ::: "memory");
          }
          if (RED_DEPTH) asm volatile("cp.async.bulk.wait_group.read 0;" ::: "memory");
          if (w == 0 && p >= 5) TSTAMP(33 + (p - 5) * 2);
          if (p < 7) mbar_arrive(sb + B_SEMPTY + (w * 2 + b) * 8);
          if (++nb == 9) nb = 0;
        }
        asm volatile("cp.async.bulk.wait_group.read 0;" ::: "memory");
        TSTAMP(44 + w);
        if (w == 0) asm volatile("red.relaxed.gpu.global.add.u64 [%0], 1;" :: "l"(&g_done) : "memory");
      }
    }
  } else {
    asm volatile("setmaxnreg.inc.sync.aligned.u32 " STR(CONS_REGS) ";");
    const int t128 = tid & 127, lane = tid & 31, warp = t128 >> 5;
    Pipe pp;
    pp.full = sb + B_FULL;
    asm volatile("mapa.shared::cluster.u32 %0, %1, %2;" : "=r"(pp.rel) : "r"(sb + B_EMPTY), "r"(t128 & 1));
    pp.sig = t128 < 2;

    uint32_t A[144];
    uint32_t m0, m1;
    float mean0, mean1, q0, q1;
    {
      const uint32_t xa = sb + ((tid >> 5) * 16 + (lane & 15)) * 128, xs = (lane >> 4) ^ (lane & 7);
      float sm[6][4] = {};
#pragma unroll
      for (int kk = 0; kk < 10; kk++) {
        if (kk < 9) {
          mbar_wait(sb + B_XFULL + 8 * kk, 0);
          if (t128 == 0 && (kk == 0 || kk == 4 || kk == 8)) TSTAMP(50 + wg * 3 + kk / 4);
#pragma unroll
          for (int i = kk * 4; i < kk * 4 + 4; i++)
            asm volatile("ldmatrix.sync.aligned.m8n8.x4.shared.b16 {%0, %1, %2, %3}, [%4];"
              : "=r"(A[i * 4]), "=r"(A[i * 4 + 1]), "=r"(A[i * 4 + 2]), "=r"(A[i * 4 + 3]) : "r"(xa + kk * 16384 + ((xs ^ ((i & 3) * 2)) << 4)) : "memory");
        }
        if (kk > 0) {
#pragma unroll
          for (int i = kk * 4 - 4; i < kk * 4; i++) {
            mma16816(sm[i & 1], &A[i * 4], 0x3f803f80u, 0x3f803f80u);
            mma16816(sm[2 + (i & 1)], &A[i * 4], A[i * 4], A[i * 4 + 2]);
            mma16816(sm[4 + (i & 1)], &A[i * 4], A[i * 4 + 1], A[i * 4 + 3]);
          }
        }
      }
      if (t128 == 0) TSTAMP(1 + wg * 16);
      __syncwarp();
      if (lane == 0) mbar_arrive(sb + B_XDONE);
      mean0 = (sm[0][0] + sm[1][0]) * (1.0f / D_); mean1 = (sm[0][2] + sm[1][2]) * (1.0f / D_);
      q0 = (lane & 4) ? sm[2][1] + sm[3][1] : sm[2][0] + sm[3][0];
      q1 = (lane & 4) ? sm[4][3] + sm[5][3] : sm[4][2] + sm[5][2];
      m0 = pack_bf16(mean0, mean0); m1 = pack_bf16(mean1, mean1);
    }
    auto center = [&](int i0, int n) {
#pragma unroll
      for (int i = i0; i < i0 + n; i++) { A[i] = hsub2_bf16(A[i], (i & 1) ? m1 : m0); asm volatile("" : "+r"(A[i])); }
    };
    center(0, 16);
    if (t128 == 0) TSTAMP(2 + wg * 16);

    const uint32_t parkT = sb + OFF_PARK + wg * 8192 + t128 * 16;
    float c10, c11, c20, c21;
    float G[32], U[32];
    {
      float S0[24], S1[24];
      float r0, r1, cf[4];
      const uint32_t uT = (sb + OFF_U + (lane & 3) * 2048 + (wg * 64 + warp * 16 + (lane >> 2)) * 8) ^ ((lane & 3) << 5);
      const uint32_t cT = sb + OFF_COEF + (lane & 3) * 16;
      auto uepi = [&](float (&S)[24], int tile, int j, int e) {
        const float r = (e >> 1) ? r1 : r0, a = S[j * 4 + e] * r, b = S[12 + j * 4 + e] * r;
        const float cr = cf[(e & 1) * 2], ci = cf[(e & 1) * 2 + 1];
        const uint32_t ad = (uT ^ ((e & 1) << 4) ^ ((e >> 1) << 6)) + (tile * 24 + j * 8 + (e & 1)) * 1024 + (tile == 0 && j == 0 ? OFF_U0 - OFF_U : 0);
        sts64f(ad, fmaf(cr, a, -ci * b), fmaf(cr, b, ci * a));
      };
      auto uall = [&](float (&S)[24], int tile, int kk, int q) {
        if (kk >= 2 && kk <= 7 && (q & 1)) uepi(S, tile, (kk - 2) >> 1, (kk & 1) * 2 + (q >> 1));
        if ((kk == 1 || kk == 3 || kk == 5) && q == 3) lds128f(cf, cT + (tile * 24 + (kk >> 1) * 8) * 8);
      };
      pp.wait(0, 0);
      kloop<48, 0, -1, true>(S0, A, pp, 0, [&](int kk, int q) {
          if (q == 3) {
            if (kk < 8) center(kk * 16 + 16, 16);
            if (kk == 1) {
              q0 = __shfl_sync(0xffffffff, q0, (lane & 28) | (lane >> 3)); q1 = __shfl_sync(0xffffffff, q1, (lane & 28) | (lane >> 3));
              asm volatile("" : "+f"(q0), "+f"(q1));
            }
            if (kk == 2) {
              q0 = std_of(fmaxf(fmaf(-mean0, mean0, q0 * (1.0f / D_)), 0.f));
              q1 = std_of(fmaxf(fmaf(-mean1, mean1, q1 * (1.0f / D_)), 0.f));
              asm volatile("" : "+f"(q0), "+f"(q1));
            }
            if (kk == 3) { r0 = rcp_bf(q0); r1 = rcp_bf(q1); asm volatile("" : "+f"(r0), "+f"(r1)); }
            if (kk == 4 && (tid >> 5) == sl) {
              if ((lane & 3) == 0) {
                sts64(sb + OFF_STAT + (lane >> 2) * 8, m0, __float_as_uint(r0));
                sts64(sb + OFF_STAT + (lane >> 2) * 8 + 64, m1, __float_as_uint(r1));
              }
              __syncwarp();
              if (lane == 0) mbar_arrive(sb + B_XROW);
            }
          }
        }, [&]() {});
      kloop<48, 1, 8>(S1, A, pp, 1, [&](int kk, int q) {
          if (kk == 0 && q == 3) {
            mbar_wait(sb + B_XDONE, 0);
          }
          uall(S0, 0, kk, q);
        }, [&]() { pin(S0); });
      kloop<48, 2, 8>(S0, A, pp, 0, [&](int kk, int q) { uall(S1, 1, kk, q); }, [&]() { pin(S1); });
      if (t128 == 0) TSTAMP(3 + wg * 16);
      kloop<64, 0, -2>(G, A, pp, 1, [&](int kk, int q) {
          uall(S0, 2, kk, q);
          if (kk == 8 && q == 3) { __syncwarp(); if (lane == 0) mbar_arrive(sb + B_URDY); }
        }, [&]() { pin(S0); });
      c10 = r0 * 0.5f; c11 = r1 * 0.5f; c20 = r0 * c10; c21 = r1 * c11;
    }
    float T[2][4];
    auto gA = [&](int i) {
#pragma unroll
      for (int e = 0; e < 4; e++) asm volatile("tanh.approx.f32 %0, %1;" : "=f"(T[i & 1][e]) : "f"(G[4 * i + e] * (e < 2 ? c10 : c11)));
    };
    auto gB = [&](int i) {};
    auto gC = [&](int i, uint32_t& o0, uint32_t& o1) {
      const float h0 = G[4 * i] * c20, h1 = G[4 * i + 1] * c20, h2 = G[4 * i + 2] * c21, h3 = G[4 * i + 3] * c21;
      o0 = pack_bf16(fmaf(h0, T[i & 1][0], h0), fmaf(h1, T[i & 1][1], h1));
      o1 = pack_bf16(fmaf(h2, T[i & 1][2], h2), fmaf(h3, T[i & 1][3], h3));
      asm volatile("" : "+r"(o0), "+r"(o1));
    };
    auto gS = [&](uint32_t base, int i) { uint32_t o0, o1; gC(i, o0, o1); sts64(base + (i >> 1) * 2048 + (i & 1) * 8, o0, o1); };
#pragma unroll 1
    for (int j = 0; j < 8; j++) {
      const uint32_t pk = parkT + j * 16384;
      kloop<64, 3, 2>(U, A, pp, j & 1, [&](int kk, int q) {
          if (kk == 0 && q == 3 && (j == 2 || j == 4 || j == 7)) {
            mbar_wait(sb + (j == 2 ? B_IDONE : j == 4 ? B_UFREE : B_HRDY), 0);
            if (j == 7) {
              pp.release(6);
              if (LAG && wg == 1) {
#pragma unroll
                for (int b = 7; b < 11; b++) pp.release(b);
              }
            }
          }
          if (kk >= 2 && q == 0) gS(pk, kk - 2);
          if (kk >= 1 && q == (kk < 8 ? 1 : 0)) gA(kk - 1);
          if (kk >= 1 && q == (kk < 8 ? 3 : 2)) gB(kk - 1);
          if (kk == 8 && q == 3) gS(pk, 7);
        }, [&]() { pin(G); });
      uint32_t sg[2][4];
      kloop<64, 0, 5>(G, A, pp, j & 1, [&](int kk, int q) {
          if (kk >= 1 && kk <= 4 && q == 0) lds128(sg[kk & 1], pk + (kk - 1) * 2048);
          if (kk >= 2 && kk <= 5 && q == 1) {
            const int i = kk - 2;
            uint32_t o[4];
#pragma unroll
            for (int e = 0; e < 4; e++) o[e] = hmul2_bf16(sg[(kk - 1) & 1][e], pack_bf16(U[8 * i + 2 * e], U[8 * i + 2 * e + 1]));
            sts128(pk + i * 2048, o);
          }
        }, [&]() { pin(U); });
      if (t128 == 0) TSTAMP(4 + j + wg * 16);
    }
    uint32_t sgk[16];
    kloop<64, 3, 2>(U, A, pp, 0, [&](int kk, int q) {
        if (kk >= 2 && q == 0) gC(kk - 2, sgk[2 * kk - 4], sgk[2 * kk - 3]);
        if (kk >= 1 && q == (kk < 8 ? 1 : 0)) gA(kk - 1);
        if (kk >= 1 && q == (kk < 8 ? 3 : 2)) gB(kk - 1);
        if (kk == 8 && q == 3) gC(7, sgk[14], sgk[15]);
      }, [&]() { pin(G); });
    if (t128 == 0) TSTAMP(12 + wg * 16);

    const uint32_t hre = DESC0 + ((OFF_H + wg * 1024) >> 4) + (((2048u >> 4) - 1u) << 16);
    const uint32_t hrem = hre + 8 * 128 + ((8u * 128u) << 16);
    const uint32_t srow = (lane >> 4) + ((lane >> 1) & 6);
    const uint32_t stT = sb + OFF_PARK + 4 * 16384 + wg * 8192 + warp * 2048 + srow * 128 + (lane & 1) * 8;
    const uint32_t stX = ((lane & 3) >> 1) ^ srow;
    auto stage = [&](float (&S)[32], int b, int j, int h) {
      sts64f(stT + (2 * b + (j >> 2)) * 16384 + ((stX ^ ((j & 3) * 2)) << 4) + h * 1024, S[j * 4 + 2 * h], S[j * 4 + 2 * h + 1]);
    };
    auto pass = [&](float (&acc)[32], float (&prv)[32], const bool first, const uint32_t ph, const bool last, auto piece) {
      if (LAG && wg == 1) {
        if (first) { wg_wait<0>(); pp.release(5); }
        if (SERIAL && last) { wg_wait<0>(); pp.release(10); pp.release(11); pin(prv); piece(-1, 0); }
        asm volatile("bar.sync 4, 256;" ::: "memory");
      }
#pragma unroll
      for (int g = 0; g < 11; g++) {
        const int kk = first ? g - 2 : g, c = first ? g : g - 9;
        const int nb = g < 10 ? g + 1 : 0;
        const uint32_t nph = (nb >= 6 && nb <= 8) || nb == 0 ? ph ^ 1 : ph;
        pp.probe(nb, nph);
        wg_fence();
        if (c == 1) wg_ss64<1, 0>(acc, mkdesc(hrem, DHI_HT), mkdesc(DESC0 + (OFF_REM >> 4) + (((1024u >> 4) - 1u) << 16), DHI_NOSW));
#pragma unroll
        for (int q = 0; q < 4; q++) {
          if (c == 0 || c == 1) {
            const uint64_t da = mkdesc(hre + c * 9 * 128 + q * 256, DHI_HT), db = mkdesc(pp.desc(g) + q * 2, DHI_SW128);
            if (g == 0 && q == 0) wg_ss64_z<1, 0>(acc, da, db); else wg_ss64<1, 0>(acc, da, db);
          } else {
            const uint64_t db = mkdesc(pp.desc(g) + q * 128, DHI_SW128);
            if (g == 0 && q == 0) wg_rs64_z<1>(acc, &A[0], db); else wg_rs64<1>(acc, &A[kk * 16 + q * 4], db);
          }
          if (q == 3) wg_commit();
          piece(g, q);
        }
        if (LAG && wg == 0 && ((g == LAG - 1 && !(SERIAL && last)) || (g == SERIAL - 1 && last))) asm volatile("bar.arrive 4, 256;" ::: "memory");
        if (c == 0) pp.wait(11, ph);
        wg_wait<1>();
        if (g == 0) { if (!first) { if (!(SERIAL && last && wg == 1)) { pp.release(10); pp.release(11); } } else if (!LAG || wg == 0) pp.release(5); }
        else if (!last) pp.release(g - 1);
        if (g < 10 || !last) pp.finish(nb, nph);
        if (g == 0) pin(prv);
        TRC(pp);
        if (g == 1) { TRC(pp); }
      }
    };
    auto wg_bar = [&]() { if (wg == 0) asm volatile("bar.sync 1, 128;" ::: "memory"); else asm volatile("bar.sync 2, 128;" ::: "memory"); };
    pass(G, U, true, 0, false, [&](int g, int q) {
        if (q == 3) {
          if (g >= 1 && g <= 7) {
#pragma unroll
            for (int i = (g > 1 ? 4 : 0); i < 8; i++) lds128(&A[(g - 1) * 16 + i * 4], parkT + (g - 1 + (i >> 2)) * 16384 + (i & 3) * 2048);
          }
          if (g >= 2 && g <= 5) {
#pragma unroll
            for (int e = 4 * (g - 2); e < 4 * (g - 1); e++) {
              A[128 + e] = hmul2_bf16(sgk[e], pack_bf16(U[2 * e], U[2 * e + 1]));
              asm volatile("" : "+r"(A[128 + e]));
            }
          }
          if ((g == 2 || g == 4) && wg == 0) {
            asm volatile("bar.sync 1, 128;" ::: "memory");
            pp.release(5 + g); pp.release(6 + g);
          }
          if (g == 9) wg_bar();
        }
      });
    if (t128 == 0) TSTAMP(13 + wg * 16);
    const uint32_t sfull = sb + B_SFULL + wg * 16, sempty = sb + B_SEMPTY + wg * 16;
    auto stage_all = [&](float (&S)[32], int b) {
#pragma unroll
      for (int j = 0; j < 16; j++) stage(S, b, j >> 1, j & 1);
      fence_async_smem(); __syncwarp();
      if (lane == 0) mbar_arrive(sfull + 8 * b);
    };
    auto drain = [&](float (&S)[32], int b, uint32_t ph, bool early, int g, int q) {
      if (g == -1) { mbar_wait(sempty + 8 * b, ph); stage_all(S, b); }
      if (g == 0 && q == 3) mbar_wait(sempty + 8 * b, ph);
      if (g >= 1 && g <= 4) stage(S, b, 2 * (g - 1) + (q >> 1), q & 1);
      if (g == 5 && q == 3 && !early) { fence_async_smem(); __syncwarp(); if (lane == 0) mbar_arrive(sfull + 8 * b); }
    };
#pragma unroll 1
    for (int it = 0; it < 4; it++) {
      pass(U, G, false, 1, false, [&](int g, int q) { drain(G, 0, (it & 1) ^ 1, false, g, q); });
      pass(G, U, false, 0, it == 3, [&](int g, int q) { drain(U, 1, (it & 1) ^ 1, SERIAL && it == 3 && wg == 1, g, q); });
    }
    mbar_wait(sempty, 1);
    wg_wait<0>();
    pin(G);
    if (t128 == 0) TSTAMP(14 + wg * 16);
    stage_all(G, 0);
  }
}

typedef CUresult (*EncodeTiledFn)(CUtensorMap*, CUtensorMapDataType, cuuint32_t, void*, const cuuint64_t*, const cuuint64_t*,
                                  const cuuint32_t*, const cuuint32_t*, CUtensorMapInterleave, CUtensorMapSwizzle,
                                  CUtensorMapL2promotion, CUtensorMapFloatOOBfill);

static void make_map(EncodeTiledFn enc, CUtensorMap* m, const void* ptr, bool f32, uint64_t inner, uint64_t outer,
                     uint32_t bi, uint32_t bo, bool swz) {
  cuuint64_t dims[2] = {inner, outer};
  cuuint64_t strides[1] = {inner * (f32 ? 4u : 2u)};
  cuuint32_t box[2] = {bi, bo}, es[2] = {1, 1};
  enc(m, f32 ? CU_TENSOR_MAP_DATA_TYPE_FLOAT32 : CU_TENSOR_MAP_DATA_TYPE_BFLOAT16, 2, const_cast<void*>(ptr), dims, strides, box, es,
      CU_TENSOR_MAP_INTERLEAVE_NONE, swz ? CU_TENSOR_MAP_SWIZZLE_128B : CU_TENSOR_MAP_SWIZZLE_NONE,
      CU_TENSOR_MAP_L2_PROMOTION_L2_128B, CU_TENSOR_MAP_FLOAT_OOB_FILL_NONE);
}

extern "C" void kernel_launch(void* const* d_in, const int* in_sizes, int n_in, void* d_out, int out_size) {
  (void)in_sizes; (void)n_in; (void)out_size;
  static EncodeTiledFn enc = nullptr;
  if (!enc) {
    void* fn = nullptr; cudaDriverEntryPointQueryResult st;
    cudaGetDriverEntryPoint("cuTensorMapEncodeTiled", &fn, cudaEnableDefault, &st);
    enc = (EncodeTiledFn)fn;
    cudaFuncSetAttribute(fused_s5_swiglu_kernel, cudaFuncAttributeMaxDynamicSharedMemorySize, SMEM_BYTES);
  }
  Params P;
  make_map(enc, &P.mx, d_in[0], false, D_, L_, 64, 128, true);
  make_map(enc, &P.mw1, d_in[10], false, F_, D_, 64, 32, true);
  make_map(enc, &P.mw3, d_in[11], false, F_, D_, 64, 32, true);
  make_map(enc, &P.mw2, d_in[12], false, D_, F_, 64, 32, true);
  make_map(enc, &P.mbre, d_in[3], false, D_, D_, 64, 24, true);
  make_map(enc, &P.mbim, d_in[4], false, D_, D_, 64, 24, true);
  make_map(enc, &P.mcre, d_in[5], false, D_, D_, 64, 32, true);
  make_map(enc, &P.mcim, d_in[6], false, D_, D_, 64, 32, true);
  make_map(enc, &P.mcre8, d_in[5], false, D_, D_, 8, 64, false);
  make_map(enc, &P.mcim8, d_in[6], false, D_, D_, 8, 64, false);
  {
    cuuint64_t dims[4] = {D_, 2, 4, L_ / 8}, strides[3] = {4 * D_ * 4, D_ * 4, 8 * D_ * 4};
    cuuint32_t box[4] = {32, 2, 4, 2}, es[4] = {1, 1, 1, 1};
    enc(&P.mout, CU_TENSOR_MAP_DATA_TYPE_FLOAT32, 4, d_out, dims, strides, box, es, CU_TENSOR_MAP_INTERLEAVE_NONE,
        CU_TENSOR_MAP_SWIZZLE_128B, CU_TENSOR_MAP_L2_PROMOTION_L2_128B, CU_TENSOR_MAP_FLOAT_OOB_FILL_NONE);
  }
  P.x = (const __nv_bfloat16*)d_in[0];
  P.lre = (const __nv_bfloat16*)d_in[1];
  P.lim = (const __nv_bfloat16*)d_in[2];
  P.logdt = (const __nv_bfloat16*)d_in[7];
  P.dskip = (const __nv_bfloat16*)d_in[8];
  P.out = (float*)d_out;
  fused_s5_swiglu_kernel<<<128, 384, SMEM_BYTES, cudaStreamPerThread>>>(P);
}
```
